```python
import torch

def _softmax(x, axis=-1):
    return torch.softmax(x, dim=axis)
def _gelu(x):
    return torch.nn.functional.gelu(x, approximate="tanh")
def _silu(x):
    return torch.nn.functional.silu(x)
def _sigmoid(x):
    return torch.sigmoid(x)
def _layernorm(x, axis=-1, eps=1e-5):
    m = x.mean(dim=axis, keepdim=True)
    v = x.var(dim=axis, keepdim=True, unbiased=False)
    return (x - m) / torch.sqrt(v + eps)
def _scatter_add(tgt, idx, src, axis=0):
    return tgt.clone().index_add_(axis, idx, src)
def _segment_sum(src, seg, n):
    out = torch.zeros((n,) + src.shape[1:], dtype=src.dtype)
    return out.index_add_(0, seg, src)
def _pad(x, pw):
    flat = tuple(v for pair in reversed(pw) for v in pair)
    return torch.nn.functional.pad(x, flat)

kernel_name = 'parallel_sum__sliding_block_cached__glu_gated_bilinear__decode'

def setup_inputs():

    _w = (lambda a: (lambda t: t.to(torch.bfloat16) if t.is_floating_point() else t)(torch.as_tensor(a)))
    def _A_setup():
        B, Sq, D = 2, 1, 448
        Hq, Hkv, Sk, Dh = 16, 8, 32768, 256
        assert Hq % Hkv == 0, (Hq, Hkv)
        return {
            "x": _w((lambda *s: torch.randn(*s, dtype=torch.bfloat16) * 0.05)(B, Sq, D)),
            "k_cache": _w((lambda *s: torch.randn(*s, dtype=torch.bfloat16) * 1.6)(B, Hkv, Sk, Dh)),
            "v_cache": _w((lambda *s: torch.randn(*s, dtype=torch.bfloat16) * 0.8)(B, Hkv, Sk, Dh)),
            "wq": _w((lambda *s: torch.randn(*s, dtype=torch.bfloat16) * 1.6)(D, Hq * Dh) * (D ** -0.5)),
            "wo": _w((lambda *s: torch.randn(*s, dtype=torch.bfloat16) * 0.8)(Hq * Dh, D) * ((Hq * Dh) ** -0.5)),
        }
    _A_in = _A_setup()

    def _B_setup():
        B, S, D, F = 2, 1, 448, 1792
        return {
            "x": _w((lambda *s: torch.randn(*s, dtype=torch.bfloat16) * 0.05)(B, S, D)),
            "w_gate": _w((lambda *s: torch.randn(*s, dtype=torch.bfloat16) * 0.4)(D, F) * (D ** -0.5)),
            "w_up": _w((lambda *s: torch.randn(*s, dtype=torch.bfloat16) * 0.4)(D, F) * (D ** -0.5)),
            "w_down": _w((lambda *s: torch.randn(*s, dtype=torch.bfloat16) * 0.4)(F, D) * (F ** -0.5)),
        }
    _B_in = _B_setup()

    return {
        "A_x": _A_in["x"],
        "A_k_cache": _A_in["k_cache"],
        "A_v_cache": _A_in["v_cache"],
        "A_wq": _A_in["wq"],
        "A_wo": _A_in["wo"],
        "B_x": _B_in["x"],
        "B_w_gate": _B_in["w_gate"],
        "B_w_up": _B_in["w_up"],
        "B_w_down": _B_in["w_down"],
    }

def reference(A_x, A_k_cache, A_v_cache, A_wq, A_wo, B_x, B_w_gate, B_w_up, B_w_down):
    def _A_ref(x, k_cache, v_cache, wq, wo):
        B, Sq, D = x.shape
        Hq, Dh = 16, 256
        Hkv, Sk = k_cache.shape[1], k_cache.shape[2]
        W = min(4096, max(256, Sk // 4))
        rep = Hq // Hkv
        q = (lambda x, *d: x.permute(*d))((x @ wq).reshape(B, Sq, Hq, Dh), 0, 2, 1, 3)
        k = (lambda x, n, axis: torch.repeat_interleave(x, n, dim=axis))(k_cache[:, :, Sk - W:, :], rep, axis=1)
        v = (lambda x, n, axis: torch.repeat_interleave(x, n, dim=axis))(v_cache[:, :, Sk - W:, :], rep, axis=1)
        scores = torch.einsum("bhqd,bhkd->bhqk", q, k) * (Dh ** -0.5)
        p = _softmax(scores, axis=-1)
        o = torch.einsum("bhqk,bhkd->bhqd", p, v)
        return (lambda x, *d: x.permute(*d))(o, 0, 2, 1, 3).reshape(B, Sq, Hq * Dh) @ wo

    def _B_ref(x, w_gate, w_up, w_down):
        g = torch.einsum("bsd,df->bsf", x, w_gate)
        u = torch.einsum("bsd,df->bsf", x, w_up)
        h = g * u
        return torch.einsum("bsf,fd->bsd", h, w_down)

    x = A_x
    xn = _layernorm(x, axis=-1)
    return x + _A_ref(xn, A_k_cache, A_v_cache, A_wq, A_wo) + _B_ref(xn, B_w_gate, B_w_up, B_w_down)
```

```cpp
#include <cuda_runtime.h>
#include <cuda_bf16.h>
#include <cuda.h>
#include <stdint.h>

namespace {

constexpr int D_   = 448;
constexpr int SK   = 32768;
constexpr int WIN  = 4096;
constexpr int FF   = 1792;
constexpr int QD   = 4096;
constexpr int NCTA = 128;
constexpr int NFF  = 112;
constexpr int NCON = 56;

constexpr int TILE_BYTES = 16384;
constexpr int WT_BYTES   = 14336;
constexpr int NR         = 13;
#define LIM_ 4
#define WAKE_ 10
constexpr int LIM = LIM_;
constexpr int NOPS = 41;

constexpr int NTHREADS = 320;
#define SPIN_ (1 << 20)
constexpr int SPIN_MAX = SPIN_;

constexpr int OFF_P    = NR * TILE_BYTES;
constexpr int OFF_XN   = OFF_P;
constexpr int OFF_Q    = OFF_P + 2048;
constexpr int OFF_ML   = OFF_P + 16384;
constexpr int OFF_H    = OFF_ML + 128;
constexpr int OFF_TAG  = OFF_H + 64;
constexpr int OFF_BAR  = OFF_TAG + 16;
constexpr int NBAR     = 2 * NR + 13;
constexpr int SMEM_BYTES = OFF_BAR + NBAR * 8 + 1024;

struct Maps { CUtensorMap m[7]; };

__device__ unsigned g_epoch;
__device__ __align__(128) uint32_t g_q[2 * QD];
__device__ __align__(128) uint32_t g_s[NCTA * 1024];
__device__ __align__(128) uint32_t g_y[NFF * D_];
__device__ __align__(128) uint32_t g_fin[NCON * 64 * 16];
#define TS(i) do {} while (0)

__device__ __forceinline__ uint32_t s2u(const void* p) { return (uint32_t)__cvta_generic_to_shared(p); }
__device__ __forceinline__ void mbar_init(uint32_t bar, int cnt) { asm volatile("mbarrier.init.shared::cta.b64 [%0], %1;" ::"r"(bar), "r"(cnt) : "memory"); }
__device__ __forceinline__ void mbar_expect(uint32_t bar, uint32_t bytes) { asm volatile("mbarrier.arrive.expect_tx.shared::cta.b64 _, [%0], %1;" ::"r"(bar), "r"(bytes) : "memory"); }
__device__ __forceinline__ void mbar_arrive(uint32_t bar, uint32_t cnt) { asm volatile("mbarrier.arrive.shared::cta.b64 _, [%0], %1;" ::"r"(bar), "r"(cnt) : "memory"); }
__device__ __forceinline__ void mbar_wait(uint32_t bar, uint32_t parity) {
    asm volatile("{\n.reg .pred p, q;\n.reg .u32 n;\nmov.u32 n, 0;\n"
                 "W_%=:\nmbarrier.try_wait.parity.shared::cta.b64 p, [%0], %1;\n"
                 "add.u32 n, n, 1;\nsetp.lt.u32 q, n, 0x400000;\nand.pred q, q, !p;\n@q bra W_%=;\n}"
                 ::"r"(bar), "r"(parity) : "memory");
}
__device__ __forceinline__ float ex2(float v) { float r; asm("ex2.approx.ftz.f32 %0, %1;" : "=f"(r) : "f"(v)); return r; }
__device__ __forceinline__ void tma3d(uint32_t dst, const CUtensorMap* tm, int c0, int c1, uint32_t bar) {
    asm volatile("cp.async.bulk.tensor.3d.shared::cluster.global.mbarrier::complete_tx::bytes [%0], [%1, {%3,%4,%5}], [%2];"
                 ::"r"(dst), "l"(tm), "r"(bar), "r"(c0), "r"(c1), "r"(0) : "memory");
}
__device__ __forceinline__ void bar_sync(int id, int n) { asm volatile("bar.sync %0, %1;" ::"r"(id), "r"(n) : "memory"); }
__device__ __forceinline__ void bar_arrive(int id, int n) { asm volatile("bar.arrive %0, %1;" ::"r"(id), "r"(n) : "memory"); }
__device__ __forceinline__ void ldsm4(uint32_t addr, uint32_t* r) {
    asm volatile("ldmatrix.sync.aligned.m8n8.x4.shared.b16 {%0,%1,%2,%3}, [%4];"
                 : "=r"(r[0]), "=r"(r[1]), "=r"(r[2]), "=r"(r[3]) : "r"(addr) : "memory");
}
__device__ __forceinline__ void ldsm4t(uint32_t addr, uint32_t* r) {
    asm volatile("ldmatrix.sync.aligned.m8n8.x4.trans.shared.b16 {%0,%1,%2,%3}, [%4];"
                 : "=r"(r[0]), "=r"(r[1]), "=r"(r[2]), "=r"(r[3]) : "r"(addr) : "memory");
}
__device__ __forceinline__ void mma16816(float* c, const uint32_t* a, uint32_t b0, uint32_t b1) {
    asm volatile("mma.sync.aligned.m16n8k16.row.col.f32.bf16.bf16.f32 {%0,%1,%2,%3}, {%4,%5,%6,%7}, {%8,%9}, {%0,%1,%2,%3};"
                 : "+f"(c[0]), "+f"(c[1]), "+f"(c[2]), "+f"(c[3])
                 : "r"(a[0]), "r"(a[1]), "r"(a[2]), "r"(a[3]), "r"(b0), "r"(b1));
}
__device__ __forceinline__ uint4 ld_relaxed4(const uint32_t* p) {
    uint4 v;
    asm volatile("ld.relaxed.gpu.global.v4.u32 {%0,%1,%2,%3}, [%4];" : "=r"(v.x), "=r"(v.y), "=r"(v.z), "=r"(v.w) : "l"(p) : "memory");
    return v;
}
__device__ __forceinline__ uint2 ld_relaxed2(const uint32_t* p) {
    uint2 v;
    asm volatile("ld.relaxed.gpu.global.v2.u32 {%0,%1}, [%2];" : "=r"(v.x), "=r"(v.y) : "l"(p) : "memory");
    return v;
}
__device__ __forceinline__ void st_relaxed(uint32_t* p, uint32_t v) { asm volatile("st.relaxed.gpu.global.u32 [%0], %1;" ::"l"(p), "r"(v) : "memory"); }
__device__ __forceinline__ void st_relaxed2(uint32_t* p, uint32_t a, uint32_t b) { asm volatile("st.relaxed.gpu.global.v2.u32 [%0], {%1,%2};" ::"l"(p), "r"(a), "r"(b) : "memory"); }
__device__ __forceinline__ float bf16r(float v) { return __bfloat162float(__float2bfloat16_rn(v)); }
__device__ __forceinline__ float bflo(uint32_t w) { return __uint_as_float(w << 16); }
__device__ __forceinline__ float bfhi(uint32_t w) { return __uint_as_float(w & 0xffff0000u); }
__device__ __forceinline__ uint32_t packbf(float lo, float hi) {
    __nv_bfloat162 v = __floats2bfloat162_rn(lo, hi);
    return *reinterpret_cast<uint32_t*>(&v);
}
__device__ __forceinline__ float sel4(const float* c, int t) { return (t & 2) ? ((t & 1) ? c[3] : c[2]) : ((t & 1) ? c[1] : c[0]); }
__device__ __forceinline__ uint32_t tagf(float v, uint32_t tag) { return (__float_as_uint(v) & ~3u) | tag; }
__device__ __forceinline__ uint32_t tagbf(float v, uint32_t tag) { return packbf(0.f, v) | tag; }
__device__ __forceinline__ float untag(uint32_t w) { return __uint_as_float(w & ~3u); }
__device__ __forceinline__ bool ok4(const uint4& v, uint32_t tag) { return (((v.x ^ tag) | (v.y ^ tag) | (v.z ^ tag) | (v.w ^ tag)) & 3u) == 0; }
__device__ __forceinline__ void poll8(uint4* v, const uint32_t* p, uint32_t tag) {
    int it = 0;
    while (true) {
        bool ok = true;
#pragma unroll
        for (int i = 0; i < 8; i++)
            if (!ok4(v[i], tag)) { v[i] = ld_relaxed4(p + i * 128); ok = false; }
        if (ok || ++it >= SPIN_MAX) break;
    }
    __syncwarp();
}

__global__ void __launch_bounds__(NTHREADS, 1)
fused_decode_kernel(const __grid_constant__ Maps maps, const __nv_bfloat16* __restrict__ x, __nv_bfloat16* __restrict__ out) {
    extern __shared__ unsigned char smem_raw[];
    const uint32_t sbase = (s2u(smem_raw) + 1023u) & ~1023u;
    unsigned char* sm = smem_raw + (sbase - s2u(smem_raw));
    const int tid = threadIdx.x, warp = tid >> 5, lane = tid & 31;
    const int cta = blockIdx.x;
    const int hkv = cta >> 4, j16 = cta & 15, b = j16 >> 3, sp = j16 & 7;
    const bool has_ffn = cta < NFF;
    const uint32_t wbar = sbase + OFF_BAR, rfull = wbar + 72, rempty = rfull + NR * 8, wempty = rempty + NR * 8;
    const int g = lane >> 2, t = lane & 3, mi = lane >> 3;
    const int krow = (mi >> 1) * 8 + (lane & 7);
    const uint32_t* sx = reinterpret_cast<const uint32_t*>(sm + OFF_XN) + (g & 1) * 224 + t;

    if (warp < 8) {
        if (tid == 0) TS(0);
        {
            const int bb = warp >> 2;
            const uint4 xa = __ldg(reinterpret_cast<const uint4*>(x + bb * D_) + lane);
            uint4 xb = make_uint4(0, 0, 0, 0);
            if (lane < 24) xb = __ldg(reinterpret_cast<const uint4*>(x + bb * D_) + 32 + lane);
            const int i4 = tid & 127;
            uint2 xo = make_uint2(0, 0);
            if (i4 < 112) xo = __ldg(reinterpret_cast<const uint2*>(x + bb * D_) + i4);
            const uint32_t e[8] = {xa.x, xa.y, xa.z, xa.w, xb.x, xb.y, xb.z, xb.w};
            float s = 0.f;
#pragma unroll
            for (int j = 0; j < 8; j++) s += bflo(e[j]) + bfhi(e[j]);
#pragma unroll
            for (int o = 16; o; o >>= 1) s += __shfl_xor_sync(0xffffffffu, s, o);
            const float mean = s * (1.f / D_);
            float v = 0.f;
#pragma unroll
            for (int j = 0; j < 8; j++) {
                const float d0 = bflo(e[j]) - mean, d1 = bfhi(e[j]) - mean;
                if (j < 4 || lane < 24) v += d0 * d0 + d1 * d1;
            }
#pragma unroll
            for (int o = 16; o; o >>= 1) v += __shfl_xor_sync(0xffffffffu, v, o);
            const float mb = bf16r(mean);
            const float den = bf16r(sqrtf(bf16r(bf16r(v * (1.f / D_)) + 1e-5f)));
            const uint32_t n0 = packbf(__fdiv_rn(bf16r(bflo(xo.x) - mb), den), __fdiv_rn(bf16r(bfhi(xo.x) - mb), den));
            const uint32_t n1 = packbf(__fdiv_rn(bf16r(bflo(xo.y) - mb), den), __fdiv_rn(bf16r(bfhi(xo.y) - mb), den));
            if (i4 < 112) reinterpret_cast<uint2*>(sm + OFF_XN + bb * 896)[i4] = make_uint2(n0, n1);
        }
        bar_sync(4, NTHREADS);
        const uint32_t tag = *reinterpret_cast<const volatile uint32_t*>(sm + OFF_TAG);

        uint32_t* sq = reinterpret_cast<uint32_t*>(sm + OFF_Q);
        if (warp < 2) {
            const uint32_t off = sbase + 6 * TILE_BYTES + krow * 64 + (((warp * 2 + (mi & 1)) ^ ((krow >> 1) & 3)) << 4);
            float c0[4] = {0.f, 0.f, 0.f, 0.f}, c1[4] = {0.f, 0.f, 0.f, 0.f};
#pragma unroll 1
            for (int hf = 0; hf < 2; hf++) {
                mbar_wait(wbar + hf * 8, 0);
#pragma unroll
                for (int ks = 0; ks < 14; ks++) {
                    uint32_t a[4];
                    ldsm4t(off + hf * TILE_BYTES + ks * 1024, a);
                    mma16816((ks & 1) ? c1 : c0, a, sx[hf * 112 + ks * 8], sx[hf * 112 + ks * 8 + 4]);
                }
            }
            st_relaxed(g_q + (t & 1) * QD + cta * 32 + warp * 16 + (t >> 1) * 8 + g, tagbf(sel4(c0, t) + sel4(c1, t), tag));
            if (lane == 0) mbar_arrive(wempty, 1);
            if (tid == 0) TS(1);
        }
        uint32_t af[4][4][4];
        float y0 = 0.f, y1 = 0.f;
        if (warp < 7) {
            const uint32_t off = sbase + 8 * TILE_BYTES + warp * 2048 + krow * 128;
#pragma unroll
            for (int j = 0; j < 4; j++) {
                mbar_wait(wbar + 32 + j * 8, 0);
#pragma unroll
                for (int m = 0; m < 4; m++) ldsm4t(off + j * TILE_BYTES + (((m * 2 + (mi & 1)) ^ (lane & 7)) << 4), af[j][m]);
                if (j == 2) {
                    __syncwarp();
                    if (lane == 0) mbar_arrive(wempty + 16, 1);
                }
            }
            float f[4] = {0.f, 0.f, 0.f, 0.f};
            if (has_ffn) {
                bar_sync(2, 256);
                const uint32_t* sH = reinterpret_cast<const uint32_t*>(sm + OFF_H);
                const uint32_t h0 = sH[(g & 1) * 8 + t], h1 = sH[(g & 1) * 8 + 4 + t];
                mbar_wait(wbar + 64, 0);
#pragma unroll
                for (int m = 0; m < 4; m++) {
                    uint32_t a[4];
                    float c[4] = {0.f, 0.f, 0.f, 0.f};
                    ldsm4t(off + 4 * TILE_BYTES + (((m * 2 + (mi & 1)) ^ (lane & 7)) << 4), a);
                    mma16816(c, a, h0, h1);
                    if (m == t) { f[0] = c[0]; f[1] = c[1]; f[2] = c[2]; f[3] = c[3]; }
                }
                y0 = b ? f[1] : f[0];
                y1 = b ? f[3] : f[2];
                st_relaxed2(g_y + cta * D_ + tid * 2, tagf(b ? f[0] : f[1], tag), tagf(b ? f[2] : f[3], tag));
            }
        } else {
            const uint32_t* p = g_q + b * QD + hkv * 512 + lane * 4;
            uint4 v[4];
            int it = 0;
            do {
#pragma unroll
                for (int i = 0; i < 4; i++) v[i] = ld_relaxed4(p + i * 128);
            } while (!(ok4(v[0], tag) && ok4(v[1], tag) && ok4(v[2], tag) && ok4(v[3], tag)) && ++it < SPIN_MAX);
#pragma unroll
            for (int i = 0; i < 4; i++)
                *reinterpret_cast<uint2*>(sq + i * 64 + lane * 2) = make_uint2(__byte_perm(v[i].x, v[i].y, 0x7632), __byte_perm(v[i].z, v[i].w, 0x7632));
            if (lane == 0) TS(2);
        }
        bar_sync(1, 256);
        if (tid == 0) mbar_arrive(wempty + 24, 1);

        {
            uint32_t qf[16][2];
#pragma unroll
            for (int ks = 0; ks < 16; ks++) {
                qf[ks][0] = sq[(g & 1) * 128 + ks * 8 + t];
                qf[ks][1] = sq[(g & 1) * 128 + ks * 8 + 4 + t];
            }
            const int row = (warp & 1) * 16 + (lane & 7) + (mi & 1) * 8;
            const uint32_t rowoff = sbase + row * 128, sw = lane & 7, uhi = lane >> 4;
            uint32_t* dst = g_s + cta * 1024 + warp * 32 + ((t & 1) * 4 + (g >> 1)) * 4 + (t >> 1) * 2 + (g & 1);
#pragma unroll 1
            for (int tl = warp >> 1; tl < 16; tl += 4) {
                const int slot = tl < NR ? tl : tl - NR;
                mbar_wait(rfull + slot * 8, tl >= NR);
                const uint32_t base = rowoff + slot * TILE_BYTES;
                float c0[4] = {0.f, 0.f, 0.f, 0.f}, c1[4] = {0.f, 0.f, 0.f, 0.f};
#pragma unroll
                for (int ks = 0; ks < 16; ks++) {
                    uint32_t a[4];
                    ldsm4(base + (ks >> 2) * 4096 + ((((ks & 3) * 2 + uhi) ^ sw) << 4), a);
                    mma16816((ks & 1) ? c1 : c0, a, qf[ks][0], qf[ks][1]);
                }
                st_relaxed(dst, tagbf(sel4(c0, t) + sel4(c1, t), tag));
                dst += 256;
                if (lane == 0) mbar_arrive(rempty + slot * 8, 4);
            }
        }
        if (tid == 0) TS(3);
        const uint32_t* ps = g_s + ((cta & ~7) + warp) * 1024 + lane * 4;
        uint4 sv[8];
#pragma unroll
        for (int i = 0; i < 8; i++) sv[i] = ld_relaxed4(ps + i * 128);

        poll8(sv, ps, tag);
        if (tid == 0) TS(4);
        {
            float e[32];
            float mx = -INFINITY;
#pragma unroll
            for (int i = 0; i < 8; i++) {
                e[i * 4 + 0] = bfhi(sv[i].x); e[i * 4 + 1] = bfhi(sv[i].y); e[i * 4 + 2] = bfhi(sv[i].z); e[i * 4 + 3] = bfhi(sv[i].w);
                mx = fmaxf(fmaxf(mx, fmaxf(e[i * 4], e[i * 4 + 1])), fmaxf(e[i * 4 + 2], e[i * 4 + 3]));
            }
#pragma unroll
            for (int o = 1; o < 32; o <<= 1)
                if (o != 4) mx = fmaxf(mx, __shfl_xor_sync(0xffffffffu, mx, o));
            const float SC = 0.0625f * 1.4426950408889634f;
            float l = 0.f;
#pragma unroll
            for (int i = 0; i < 32; i++) { e[i] = ex2((e[i] - mx) * SC); l += e[i]; }
#pragma unroll
            for (int o = 1; o < 32; o <<= 1)
                if (o != 4) l += __shfl_xor_sync(0xffffffffu, l, o);
            float2* sML = reinterpret_cast<float2*>(sm + OFF_ML) + (g & 1) * 8;
            if ((lane & ~4) == 0) sML[warp] = make_float2(mx, l);
            bar_sync(1, 256);
            float M = mx, L = 0.f;
#pragma unroll
            for (int k = 0; k < 8; k++) M = fmaxf(M, sML[k].x);
#pragma unroll
            for (int k = 0; k < 8; k++) L += sML[k].y * ex2((sML[k].x - M) * SC);
            const float r = __fdiv_rn(ex2((mx - M) * SC), L);
            uint2* sP = reinterpret_cast<uint2*>(sm + OFF_P + warp * 2048) + (lane >> 4) * 16 + (lane & 7) * 2 + (mi & 1);
#pragma unroll
            for (int i = 0; i < 8; i++)
                sP[i * 32] = make_uint2(packbf(e[i * 4] * r, e[i * 4 + 1] * r), packbf(e[i * 4 + 2] * r, e[i * 4 + 3] * r));
            __syncwarp();
        }
        uint2 yp = make_uint2(tag, tag);
        const uint32_t* py = g_y + (cta ^ 8) * D_ + tid * 2;
        {
            const uint4* sP4 = reinterpret_cast<const uint4*>(sm + OFF_P + warp * 2048) + (g & 1) * 4 + t;
            const uint32_t off0 = sbase + (warp * 32 + krow) * 64 + (((mi & 1) ^ ((krow >> 1) & 3)) << 4);
            float o0[4] = {0.f, 0.f, 0.f, 0.f}, o1[4] = {0.f, 0.f, 0.f, 0.f};
            float o2[4] = {0.f, 0.f, 0.f, 0.f}, o3[4] = {0.f, 0.f, 0.f, 0.f};
#pragma unroll 1
            for (int tl = 0; tl < 16; tl++) {
                const int slot = tl < 2 * NR - 16 ? tl + 16 - NR : tl + 16 - 2 * NR;
                const uint4 pf = sP4[tl * 8];
                if (tl == WAKE_) {
                    if (has_ffn && warp < 7) yp = ld_relaxed2(py);
                    if (warp == 7 && cta < NCON) bar_arrive(3, 64);
                }
                mbar_wait(rfull + slot * 8, tl < 2 * NR - 16);
                const uint32_t base = off0 + slot * TILE_BYTES;
                uint32_t a0[4], a1[4], a2[4], a3[4];
                ldsm4t(base, a0);
                ldsm4t(base ^ 32, a1);
                ldsm4t(base + 1024, a2);
                ldsm4t((base ^ 32) + 1024, a3);
                mma16816(o0, a0, pf.x, pf.y);
                mma16816(o1, a1, pf.x, pf.y);
                mma16816(o2, a2, pf.z, pf.w);
                mma16816(o3, a3, pf.z, pf.w);
                if (tl < 16 - NR && lane == 0) mbar_arrive(rempty + slot * 8, 1);
            }
            __syncwarp();
            float* sO = reinterpret_cast<float*>(sm + OFF_P + warp * 2048) + t * 8 + g;
            sO[0]  = (t & 2) ? ((t & 1) ? o1[2] + o3[2] : o1[0] + o3[0]) : ((t & 1) ? o0[2] + o2[2] : o0[0] + o2[0]);
            sO[32] = (t & 2) ? ((t & 1) ? o1[3] + o3[3] : o1[1] + o3[1]) : ((t & 1) ? o0[3] + o2[3] : o0[1] + o2[1]);
        }
        if (tid == 0) TS(5);
        if (warp == 7) {
            bar_arrive(1, 256);
        } else {
            int it = 0;
            while ((((yp.x ^ tag) | (yp.y ^ tag)) & 3u) && ++it < SPIN_MAX) yp = ld_relaxed2(py);
            y0 += untag(yp.x);
            y1 += untag(yp.y);
            bar_sync(1, 256);
            const float2* sO2 = reinterpret_cast<const float2*>(sm + OFF_P) + lane;
            float2 s0 = sO2[0], s1 = sO2[256];
#pragma unroll
            for (int k = 2; k < 8; k += 2) {
                const float2 u0 = sO2[k * 256], u1 = sO2[k * 256 + 256];
                s0.x += u0.x; s0.y += u0.y; s1.x += u1.x; s1.y += u1.y;
            }
            const uint32_t ob = packbf(s0.x + s1.x, s0.y + s1.y);
            float acc[4][4];
#pragma unroll
            for (int m = 0; m < 4; m++) acc[m][0] = acc[m][1] = acc[m][2] = acc[m][3] = 0.f;
#pragma unroll
            for (int j = 0; j < 4; j++) {
                const uint32_t b0 = __shfl_sync(0xffffffffu, ob, j * 8 + t), b1 = __shfl_sync(0xffffffffu, ob, j * 8 + 4 + t);
#pragma unroll
                for (int m = 0; m < 4; m++) mma16816(acc[m], af[j][m], b0, b1);
            }
            y0 += (t & 2) ? ((t & 1) ? acc[3][0] : acc[2][0]) : ((t & 1) ? acc[1][0] : acc[0][0]);
            y1 += (t & 2) ? ((t & 1) ? acc[3][2] : acc[2][2]) : ((t & 1) ? acc[1][2] : acc[0][2]);
            st_relaxed2(g_fin + ((b * 28 + warp * 4 + t) * 64 + hkv * 8 + sp) * 16 + g * 2, tagf(y0, tag), tagf(y1, tag));
            if (tid == 0) TS(6);
        }
    } else if (warp == 8) {
        const int rowb = (b * 8 + hkv) * SK + (SK - WIN);
        uint32_t pend[LIM];
#pragma unroll
        for (int i = 0; i < LIM; i++) pend[i] = 0;
        if (lane == 0) {
#pragma unroll
            for (int i = 0; i < 4; i++) mbar_init(wbar + i * 8, 1);
#pragma unroll
            for (int i = 0; i < 3; i++) mbar_init(rfull + i * 8, 1);
            asm volatile("fence.mbarrier_init.release.cluster;" ::: "memory");
        }
#pragma unroll 1
        for (int i = 0; i < NOPS; i++) {
            if (i == (LIM < 7 ? LIM : 7)) {
                if (lane == 0) {
#pragma unroll
                    for (int k = 4; k < NBAR; k++)
                        if (k < 9 || k >= 12) mbar_init(wbar + k * 8, k < 9 + NR ? 1 : k < 9 + 2 * NR ? 8 : k == NBAR - 4 ? 2 : k == NBAR - 2 ? 7 : 1);
                    asm volatile("fence.mbarrier_init.release.cluster;" ::: "memory");
                }
                __syncwarp();
                bar_arrive(4, NTHREADS);
            }
            int map, c0 = 0, c1 = 0, slot;
            uint32_t bar, par = 0, bytes = WT_BYTES;
            if (i < 2 || (i < 16 && (i & 1))) {
                const int w = (i + 1) >> 1;
                if (!has_ffn && (w == 2 || w == 3 || w == 8)) continue;
                if (w == 7 && has_ffn) mbar_wait(wempty + 8, 0);
                map = w < 2 ? 2 : w < 4 ? w + 1 : w < 8 ? 5 : 6;
                c0 = w < 2 ? cta * 32 : w < 4 ? cta * 16 : 0;
                c1 = w < 4 ? (w == 1 ? 224 : 0) : w < 8 ? hkv * 512 + (w & 2) * 128 + sp * 32 + (w & 1) * 16 : cta * 16;
                slot = w < 2 ? w + 6 : w < 4 ? w + 9 : w + 4;
                bar = wbar + w * 8;
            } else {
                const int r = i < 16 ? (i >> 1) - 1 : i - 9;
                slot = r < NR ? r : r < 2 * NR ? r - NR : r - 2 * NR;
                par = r >= NR && r < 2 * NR;
                if (r >= NR) mbar_wait(rempty + slot * 8, par ^ 1);
                if (r == 6 || r == 8 || r == 11) mbar_wait(wempty + (r == 6 ? 0 : r == 8 ? 16 : 24), 0);
                map = r >> 4;
                c0 = map * sp * 32;
                c1 = rowb + (r & 15) * 256 + (map ? 0 : sp * 32);
                bar = rfull + slot * 8;
                bytes = TILE_BYTES;
            }
            if (pend[0]) mbar_wait(pend[0] & ~1u, pend[0] & 1u);
#pragma unroll
            for (int k = 0; k + 1 < LIM; k++) pend[k] = pend[k + 1];
            pend[LIM - 1] = bar | par;
            if (lane == 0) {
                mbar_expect(bar, bytes);
                tma3d(sbase + slot * TILE_BYTES, &maps.m[map], c0, c1, bar);
            }
        }
    } else {
        const unsigned epoch = *reinterpret_cast<volatile unsigned*>(&g_epoch);
        const uint32_t tag = epoch % 3u + 1u;
        if (lane == 0) *reinterpret_cast<volatile uint32_t*>(sm + OFF_TAG) = tag;
        uint32_t xv = 0;
        if (cta < NCON && lane < 8) xv = __ldg(reinterpret_cast<const uint32_t*>(x) + cta * 8 + lane);
        bar_sync(4, NTHREADS);
        if (has_ffn) {
            const uint32_t off = sbase + 11 * TILE_BYTES + krow * 32 + (((mi & 1) ^ ((krow >> 2) & 1)) << 4);
            float gu[2];
#pragma unroll 1
            for (int mat = 0; mat < 2; mat++) {
                float c0[4] = {0.f, 0.f, 0.f, 0.f}, c1[4] = {0.f, 0.f, 0.f, 0.f};
                mbar_wait(wbar + 16 + mat * 8, 0);
#pragma unroll 2
                for (int ks = 0; ks < 28; ks += 2) {
                    uint32_t a0[4], a1[4];
                    ldsm4t(off + mat * TILE_BYTES + ks * 512, a0);
                    ldsm4t(off + mat * TILE_BYTES + ks * 512 + 512, a1);
                    mma16816(c0, a0, sx[ks * 8], sx[ks * 8 + 4]);
                    mma16816(c1, a1, sx[ks * 8 + 8], sx[ks * 8 + 12]);
                }
                gu[1] = bf16r(sel4(c0, t) + sel4(c1, t));
                if (mat == 0) gu[0] = gu[1];
            }
            reinterpret_cast<__nv_bfloat16*>(sm + OFF_H)[(t & 1) * 16 + (t >> 1) * 8 + g] = __float2bfloat16_rn(gu[0] * gu[1]);
            if (lane == 0) mbar_arrive(wempty + 8, 1);
            bar_arrive(2, 256);
            if (lane == 0) TS(10);
        }
        if (cta < NCON) {
            uint4 v[8];
#pragma unroll
            for (int i = 0; i < 8; i++) v[i] = make_uint4(0, 0, 0, 0);
            bar_sync(3, 64);
            poll8(v, g_fin + cta * 1024 + lane * 4, tag);
            float r[4] = {0.f, 0.f, 0.f, 0.f};
#pragma unroll
            for (int i = 0; i < 8; i++) { r[0] += untag(v[i].x); r[1] += untag(v[i].y); r[2] += untag(v[i].z); r[3] += untag(v[i].w); }
            float lo = (lane & 4) ? r[1] : r[0], hi = (lane & 4) ? r[3] : r[2];
            lo += __shfl_xor_sync(0xffffffffu, (lane & 4) ? r[0] : r[1], 4);
            hi += __shfl_xor_sync(0xffffffffu, (lane & 4) ? r[2] : r[3], 4);
#pragma unroll
            for (int o = 8; o < 32; o <<= 1) {
                lo += __shfl_xor_sync(0xffffffffu, lo, o);
                hi += __shfl_xor_sync(0xffffffffu, hi, o);
            }
            if (lane < 8) reinterpret_cast<uint32_t*>(out)[cta * 8 + lane] = packbf(bflo(xv) + lo, bfhi(xv) + hi);
            if (cta == 0 && lane == 0) *reinterpret_cast<volatile unsigned*>(&g_epoch) = epoch + 1;
            if (lane == 0) TS(8);
        }
    }
}

typedef CUresult (*EncodeFn)(CUtensorMap*, CUtensorMapDataType, cuuint32_t, void*, const cuuint64_t*, const cuuint64_t*,
                             const cuuint32_t*, const cuuint32_t*, CUtensorMapInterleave, CUtensorMapSwizzle,
                             CUtensorMapL2promotion, CUtensorMapFloatOOBfill);

void make_map(EncodeFn enc, CUtensorMap* m, const void* ptr, uint64_t d0, uint64_t d1, uint64_t d2, uint64_t s1, uint64_t s2,
              uint32_t b0, uint32_t b1, uint32_t b2, CUtensorMapL2promotion promo) {
    cuuint64_t gd[3] = {d0, d1, d2};
    cuuint64_t gs[2] = {s1, s2};
    cuuint32_t bx[3] = {b0, b1, b2};
    cuuint32_t es[3] = {1, 1, 1};
    enc(m, CU_TENSOR_MAP_DATA_TYPE_BFLOAT16, 3, const_cast<void*>(ptr), gd, gs, bx, es, CU_TENSOR_MAP_INTERLEAVE_NONE,
        b0 == 64 ? CU_TENSOR_MAP_SWIZZLE_128B : b0 == 32 ? CU_TENSOR_MAP_SWIZZLE_64B : CU_TENSOR_MAP_SWIZZLE_32B, promo,
        CU_TENSOR_MAP_FLOAT_OOB_FILL_NONE);
}

}

extern "C" void kernel_launch(void* const* d_in, const int* in_sizes, int n_in, void* d_out, int out_size) {
    (void)in_sizes; (void)n_in; (void)out_size;
    static EncodeFn enc = nullptr;
    static Maps maps;
    static const void* cached[9] = {};
    if (!enc) {
        cudaDriverEntryPointQueryResult qr;
        void* fn = nullptr;
        cudaGetDriverEntryPoint("cuTensorMapEncodeTiled", &fn, cudaEnableDefault, &qr);
        enc = (EncodeFn)fn;
        cudaFuncSetAttribute(fused_decode_kernel, cudaFuncAttributeMaxDynamicSharedMemorySize, SMEM_BYTES);
    }
    bool same = true;
    for (int i = 0; i < 9; i++) same = same && cached[i] == d_in[i];
    if (!same) {
        const uint64_t R = (uint64_t)16 * SK;
        const CUtensorMapL2promotion P128 = CU_TENSOR_MAP_L2_PROMOTION_L2_128B, P256 = CU_TENSOR_MAP_L2_PROMOTION_L2_256B;
        make_map(enc, &maps.m[0], d_in[1], 64, R, 4, 512, 128, 64, 32, 4, P256);
        make_map(enc, &maps.m[1], d_in[2], 256, R, 1, 512, R * 512, 32, 256, 1, P256);
        make_map(enc, &maps.m[2], d_in[3], QD, D_, 1, QD * 2, (uint64_t)D_ * QD * 2, 32, 224, 1, P256);
        make_map(enc, &maps.m[3], d_in[6], FF, 224, 2, FF * 2, 224 * FF * 2, 16, 224, 2, P256);
        make_map(enc, &maps.m[4], d_in[7], FF, 224, 2, FF * 2, 224 * FF * 2, 16, 224, 2, P256);
        make_map(enc, &maps.m[5], d_in[4], 64, QD, 7, 896, 128, 64, 16, 7, P128);
        make_map(enc, &maps.m[6], d_in[8], 64, FF, 7, 896, 128, 64, 16, 7, P128);
        for (int i = 0; i < 9; i++) cached[i] = d_in[i];
    }
    fused_decode_kernel<<<NCTA, NTHREADS, SMEM_BYTES>>>(maps, (const __nv_bfloat16*)d_in[0], (__nv_bfloat16*)d_out);
}
```

```cpp
#include <cuda_runtime.h>
#include <cuda_bf16.h>
#include <cuda.h>
#include <stdint.h>

namespace {

constexpr int D_   = 448;
constexpr int SK   = 32768;
constexpr int WIN  = 4096;
constexpr int FF   = 1792;
constexpr int QD   = 4096;
constexpr int NCTA = 128;

constexpr int TILE_BYTES = 16384;
constexpr int WT_BYTES   = 14336;
constexpr int NR         = 13;
#define LIM_ 4
#define HOLD_ 2
#define LMAX_ 0
#define TAU_ 660
#define TA_ (-1540)
#define CLR_ 2
#define PRE_ 1
#define EVF 0x1f
constexpr int LIM = LIM_;
constexpr int OP_G = 2, OP_K = 4, OP_V = 20, OP_T = 36, NOPS = 39;

constexpr int NTHREADS = 320;
#define SPIN_ (1 << 20)
constexpr int SPIN_MAX = SPIN_;
constexpr float SC = 0.0625f * 1.4426950408889634f;

constexpr int OFF_P    = NR * TILE_BYTES;
constexpr int OFF_W    = OFF_P + 2048;
constexpr int OFF_Q    = OFF_W + 2048;
constexpr int OFF_XN   = OFF_Q + 1024;
constexpr int OFF_ML   = OFF_XN + 1792;
constexpr int OFF_TAG  = OFF_ML + 128;
constexpr int OFF_BAR  = OFF_TAG + 16;
constexpr int SMEM_BYTES = OFF_BAR + (2 * NR + 2) * 8;

struct Maps { CUtensorMap m[7]; };

__device__ unsigned g_epoch[8 * 32];
__device__ __align__(128) uint32_t g_q[2 * QD];
__device__ __align__(128) uint32_t g_ml[NCTA * 8];
__device__ __align__(128) uint32_t g_h[2 * FF];
__device__ __align__(128) uint32_t g_o[NCTA * 512];
__device__ __align__(128) uint32_t g_init[32];
#define TS(i) do {} while (0)

__device__ __forceinline__ uint32_t s2u(const void* p) { return (uint32_t)__cvta_generic_to_shared(p); }
__device__ __forceinline__ void mbar_init(uint32_t bar, int cnt) { asm volatile("mbarrier.init.shared::cta.b64 [%0], %1;" ::"r"(bar), "r"(cnt) : "memory"); }
__device__ __forceinline__ void mbar_expect(uint32_t bar, uint32_t bytes) { asm volatile("mbarrier.arrive.expect_tx.shared::cta.b64 _, [%0], %1;" ::"r"(bar), "r"(bytes) : "memory"); }
__device__ __forceinline__ void mbar_arrive(uint32_t bar, uint32_t cnt) { asm volatile("mbarrier.arrive.shared::cta.b64 _, [%0], %1;" ::"r"(bar), "r"(cnt) : "memory"); }
__device__ __forceinline__ void mbar_wait(uint32_t bar, uint32_t parity) {
    asm volatile("{\n.reg .pred p, q;\n.reg .u32 n;\nmov.u32 n, 0;\n"
                 "W_%=:\nmbarrier.try_wait.parity.shared::cta.b64 p, [%0], %1;\n"
                 "add.u32 n, n, 1;\nsetp.lt.u32 q, n, 0x400000;\nand.pred q, q, !p;\n@q bra W_%=;\n}"
                 ::"r"(bar), "r"(parity) : "memory");
}
__device__ __forceinline__ bool mbar_test(uint32_t bar, uint32_t parity) {
    uint32_t r;
    asm volatile("{\n.reg .pred p;\nmbarrier.test_wait.parity.shared::cta.b64 p, [%1], %2;\nselp.u32 %0, 1, 0, p;\n}" : "=r"(r) : "r"(bar), "r"(parity) : "memory");
    return r;
}
__device__ __forceinline__ uint32_t gtime32() { uint32_t t; asm volatile("mov.u32 %0, %globaltimer_lo;" : "=r"(t) :: "memory"); return t; }
__device__ __forceinline__ float ex2(float v) { float r; asm("ex2.approx.ftz.f32 %0, %1;" : "=f"(r) : "f"(v)); return r; }
__device__ __forceinline__ void tma3d(uint32_t dst, const CUtensorMap* tm, int c0, int c1, uint32_t bar, uint64_t pol) {
    asm volatile("cp.async.bulk.tensor.3d.shared::cluster.global.mbarrier::complete_tx::bytes.L2::cache_hint [%0], [%1, {%3,%4,%5}], [%2], %6;"
                 ::"r"(dst), "l"(tm), "r"(bar), "r"(c0), "r"(c1), "r"(0), "l"(pol) : "memory");
}
__device__ __forceinline__ void bar_sync(int id, int n) { asm volatile("bar.sync %0, %1;" ::"r"(id), "r"(n) : "memory"); }
__device__ __forceinline__ void bar_arrive(int id, int n) { asm volatile("bar.arrive %0, %1;" ::"r"(id), "r"(n) : "memory"); }
__device__ __forceinline__ void ldsm4(uint32_t addr, uint32_t* r) {
    asm volatile("ldmatrix.sync.aligned.m8n8.x4.shared.b16 {%0,%1,%2,%3}, [%4];"
                 : "=r"(r[0]), "=r"(r[1]), "=r"(r[2]), "=r"(r[3]) : "r"(addr) : "memory");
}
__device__ __forceinline__ void ldsm4t(uint32_t addr, uint32_t* r) {
    asm volatile("ldmatrix.sync.aligned.m8n8.x4.trans.shared.b16 {%0,%1,%2,%3}, [%4];"
                 : "=r"(r[0]), "=r"(r[1]), "=r"(r[2]), "=r"(r[3]) : "r"(addr) : "memory");
}
__device__ __forceinline__ void mma16816(float* c, const uint32_t* a, uint32_t b0, uint32_t b1) {
    asm volatile("mma.sync.aligned.m16n8k16.row.col.f32.bf16.bf16.f32 {%0,%1,%2,%3}, {%4,%5,%6,%7}, {%8,%9}, {%0,%1,%2,%3};"
                 : "+f"(c[0]), "+f"(c[1]), "+f"(c[2]), "+f"(c[3])
                 : "r"(a[0]), "r"(a[1]), "r"(a[2]), "r"(a[3]), "r"(b0), "r"(b1));
}
__device__ __forceinline__ uint4 ld_relaxed4(const uint32_t* p) {
    uint4 v;
    asm volatile("ld.relaxed.gpu.global.v4.u32 {%0,%1,%2,%3}, [%4];" : "=r"(v.x), "=r"(v.y), "=r"(v.z), "=r"(v.w) : "l"(p) : "memory");
    return v;
}
__device__ __forceinline__ void ld_relaxed4_if(uint4& v, const uint32_t* p, bool c) {
    asm volatile("{\n.reg .pred p;\nsetp.ne.u32 p, %5, 0;\n@p ld.relaxed.gpu.global.v4.u32 {%0,%1,%2,%3}, [%4];\n}"
                 : "+r"(v.x), "+r"(v.y), "+r"(v.z), "+r"(v.w) : "l"(p), "r"((uint32_t)c) : "memory");
}
__device__ __forceinline__ uint2 ld_relaxed2(const uint32_t* p) {
    uint2 v;
    asm volatile("ld.relaxed.gpu.global.v2.u32 {%0,%1}, [%2];" : "=r"(v.x), "=r"(v.y) : "l"(p) : "memory");
    return v;
}
__device__ __forceinline__ void st_relaxed(uint32_t* p, uint32_t v) { asm volatile("st.relaxed.gpu.global.u32 [%0], %1;" ::"l"(p), "r"(v) : "memory"); }
__device__ __forceinline__ void st_relaxed2(uint32_t* p, uint32_t a, uint32_t b) { asm volatile("st.relaxed.gpu.global.v2.u32 [%0], {%1,%2};" ::"l"(p), "r"(a), "r"(b) : "memory"); }
__device__ __forceinline__ float bf16r(float v) { return __bfloat162float(__float2bfloat16_rn(v)); }
__device__ __forceinline__ float bflo(uint32_t w) { return __uint_as_float(w << 16); }
__device__ __forceinline__ float bfhi(uint32_t w) { return __uint_as_float(w & 0xffff0000u); }
__device__ __forceinline__ uint32_t packbf(float lo, float hi) {
    __nv_bfloat162 v = __floats2bfloat162_rn(lo, hi);
    return *reinterpret_cast<uint32_t*>(&v);
}
__device__ __forceinline__ float sel4(const float* c, int t) { return (t & 2) ? ((t & 1) ? c[3] : c[2]) : ((t & 1) ? c[1] : c[0]); }
__device__ __forceinline__ float pick(const float* o0, const float* o1, const float* o2, const float* o3, int t, int i) {
    const float a = (t & 2) ? ((t & 1) ? o1[i + 1] : o1[i]) : ((t & 1) ? o0[i + 1] : o0[i]);
    const float c = (t & 2) ? ((t & 1) ? o3[i + 1] : o3[i]) : ((t & 1) ? o2[i + 1] : o2[i]);
    return a + c;
}
__device__ __forceinline__ uint32_t tagf(float v, uint32_t tag) { return (__float_as_uint(v) & ~3u) | tag; }
__device__ __forceinline__ uint32_t tagbf(float v, uint32_t tag) { return packbf(0.f, v) | tag; }
__device__ __forceinline__ float untag(uint32_t w) { return __uint_as_float(w & ~3u); }
__device__ __forceinline__ bool ok4(const uint4& v, uint32_t tag) { return (((v.x ^ tag) | (v.y ^ tag) | (v.z ^ tag) | (v.w ^ tag)) & 3u) == 0; }

__global__ void __launch_bounds__(NTHREADS, 1)
fused_decode_kernel(const __grid_constant__ Maps maps, const __nv_bfloat16* __restrict__ x, __nv_bfloat16* __restrict__ out) {
    extern __shared__ __align__(1024) unsigned char sm[];
    const uint32_t sbase = s2u(sm);
    const int tid = threadIdx.x, warp = tid >> 5, lane = tid & 31;
    const int cta = blockIdx.x;
    const int hkv = cta >> 4, j16 = cta & 15, b = j16 >> 3, sp = j16 & 7;
    const bool has_ffn = j16 >= 2, has_tail = j16 < 14;
    const uint32_t full = sbase + OFF_BAR, empty = full + NR * 8, hold = empty + NR * 8;

    if (warp == 8) {
        const int rowb = (b * 8 + hkv) * SK + (SK - WIN) + sp * 512;
        uint64_t polF, polN;
        asm volatile("createpolicy.fractional.L2::evict_first.b64 %0, 1.0;" : "=l"(polF));
        asm volatile("createpolicy.fractional.L2::evict_normal.b64 %0, 1.0;" : "=l"(polN));
        if (lane == 0) {
#pragma unroll
            for (int i = 0; i < 4; i++) mbar_init(full + i * 8, 1);
            asm volatile("fence.mbarrier_init.release.cluster;" ::: "memory");
#pragma unroll
            for (int i = 0; i < 4; i++) {
                if (i < 2 || has_ffn) {
                    mbar_expect(full + i * 8, WT_BYTES);
                    tma3d(sbase + i * TILE_BYTES, &maps.m[i < 2 ? 2 : i + 1], i < 2 ? cta * 32 : hkv * 224 + (j16 - 2) * 16, i == 1 ? 224 : 0,
                          full + i * 8, (EVF & 4) ? polF : polN);
                } else {
                    mbar_arrive(full + i * 8, 1);
                }
            }
            TS(11);
#pragma unroll
            for (int i = 4; i < 2 * NR + 2; i++) mbar_init(full + i * 8, i < NR || i == 2 * NR + 1 ? 1 : 8);
            asm volatile("fence.mbarrier_init.release.cluster;" ::: "memory");
        }
        __syncwarp();
        bar_arrive(4, NTHREADS);
        const int nops = has_tail ? NOPS : OP_T;
        const uint32_t t0 = LMAX_ ? gtime32() + (uint32_t)(TA_) : 0;
#pragma unroll 1
        for (int i = OP_K; i < nops; i++) {
            const int slot = i < NR ? i : i < 2 * NR ? i - NR : i - 2 * NR;
            const int j = i - LIM, sj = j < NR ? j : j < 2 * NR ? j - NR : j - 2 * NR;
            int map, c0, c1;
            uint32_t bytes = TILE_BYTES;
            if (i < OP_T) { map = i >= OP_V; c0 = 0; c1 = rowb + ((i - OP_K) & 15) * 32; }
            else if (i == OP_T) { map = 5; c0 = j16 * 32; c1 = hkv * 224; bytes = WT_BYTES; }
            else { map = 6; c0 = j16 * 32; c1 = hkv * 512 + (i - OP_T - 1) * 256; }
            if (i >= NR) mbar_wait(empty + slot * 8, i >= 2 * NR);
            if (LMAX_) {
                const int k = i - LMAX_, sk = k < NR ? k : k < 2 * NR ? k - NR : k - 2 * NR;
                if (k >= 0) mbar_wait(full + sk * 8, k >= NR && k < 2 * NR);
                while (!mbar_test(full + sj * 8, j >= NR && j < 2 * NR) && (int)(gtime32() - t0) < i * TAU_) {}
                __syncwarp();
            } else if (LIM <= OP_K || j >= 0) {
                mbar_wait(full + sj * 8, j >= NR && j < 2 * NR);
            }
            if (HOLD_ && i == NOPS - HOLD_) mbar_wait(hold, 0);
            if (lane == 0) {
                mbar_expect(full + slot * 8, bytes);
                tma3d(sbase + slot * TILE_BYTES, &maps.m[map], c0, c1, full + slot * 8, ((EVF >> map) & 1) ? polF : polN);
            }
        }
        return;
    }
    const int g = lane >> 2, t = lane & 3, mi = lane >> 3;
    const int krow = (mi >> 1) * 8 + (lane & 7);
    const uint32_t* sx = reinterpret_cast<const uint32_t*>(sm + OFF_XN) + (g & 1) * 224 + t;

    if (warp < 8) {
        if (tid == 0) TS(0);
        uint32_t* gq = g_q + (t & 1) * QD + cta * 32 + warp * 16 + (t >> 1) * 8 + g;
        {
            const int bb = warp >> 2;
            const uint4 xa = __ldg(reinterpret_cast<const uint4*>(x + bb * D_) + lane);
            uint4 xb = make_uint4(0, 0, 0, 0);
            if (lane < 24) xb = __ldg(reinterpret_cast<const uint4*>(x + bb * D_) + 32 + lane);
            const int i4 = tid & 127;
            uint2 xo = make_uint2(0, 0);
            if (i4 < 112) xo = __ldg(reinterpret_cast<const uint2*>(x + bb * D_) + i4);
            const uint32_t e[8] = {xa.x, xa.y, xa.z, xa.w, xb.x, xb.y, xb.z, xb.w};
            float s = 0.f;
#pragma unroll
            for (int j = 0; j < 8; j++) s += bflo(e[j]) + bfhi(e[j]);
#pragma unroll
            for (int o = 16; o; o >>= 1) s += __shfl_xor_sync(0xffffffffu, s, o);
            const float mean = s * (1.f / D_);
            float v = 0.f;
#pragma unroll
            for (int j = 0; j < 8; j++) {
                const float d0 = bflo(e[j]) - mean, d1 = bfhi(e[j]) - mean;
                if (j < 4 || lane < 24) v += d0 * d0 + d1 * d1;
            }
#pragma unroll
            for (int o = 16; o; o >>= 1) v += __shfl_xor_sync(0xffffffffu, v, o);
            const float mb = bf16r(mean);
            const float den = bf16r(sqrtf(bf16r(bf16r(v * (1.f / D_)) + 1e-5f)));
            const uint32_t n0 = packbf(__fdiv_rn(bf16r(bflo(xo.x) - mb), den), __fdiv_rn(bf16r(bfhi(xo.x) - mb), den));
            const uint32_t n1 = packbf(__fdiv_rn(bf16r(bflo(xo.y) - mb), den), __fdiv_rn(bf16r(bfhi(xo.y) - mb), den));
            if (i4 < 112) reinterpret_cast<uint2*>(sm + OFF_XN + bb * 896)[i4] = make_uint2(n0, n1);
        }
        bar_sync(4, NTHREADS);
        const uint32_t tag = *reinterpret_cast<const volatile uint32_t*>(sm + OFF_TAG);

        uint32_t* sq = reinterpret_cast<uint32_t*>(sm + OFF_Q);
        if (warp < 2) {
            const uint32_t off = sbase + krow * 64 + (((warp * 2 + (mi & 1)) ^ ((krow >> 1) & 3)) << 4);
            float c0[4] = {0.f, 0.f, 0.f, 0.f}, c1[4] = {0.f, 0.f, 0.f, 0.f};
#pragma unroll 1
            for (int hf = 0; hf < 2; hf++) {
                mbar_wait(full + hf * 8, 0);
#pragma unroll
                for (int ks = 0; ks < 14; ks++) {
                    uint32_t a[4];
                    ldsm4t(off + hf * TILE_BYTES + ks * 1024, a);
                    mma16816((ks & 1) ? c1 : c0, a, sx[hf * 112 + ks * 8], sx[hf * 112 + ks * 8 + 4]);
                }
            }
            st_relaxed(gq, tagbf(sel4(c0, t) + sel4(c1, t), tag));
            if (lane < 2) mbar_arrive(empty + lane * 8, 4);
            if (tid == 0) TS(1);
        } else if (warp == 7) {
            const uint32_t* p = g_q + b * QD + hkv * 512 + lane * 4;
            uint4 v[4];
            int it = 0;
            mbar_wait(full + 8, 0);
            do {
#pragma unroll
                for (int i = 0; i < 4; i++) v[i] = ld_relaxed4(p + i * 128);
            } while (!(ok4(v[0], tag) && ok4(v[1], tag) && ok4(v[2], tag) && ok4(v[3], tag)) && ++it < SPIN_MAX);
#pragma unroll
            for (int i = 0; i < 4; i++)
                *reinterpret_cast<uint2*>(sq + i * 64 + lane * 2) = make_uint2(__byte_perm(v[i].x, v[i].y, 0x7632), __byte_perm(v[i].z, v[i].w, 0x7632));
            if (lane == 0) TS(2);
        }
        bar_sync(1, 256);

        {
            uint32_t qf[16][2];
#pragma unroll
            for (int ks = 0; ks < 16; ks++) {
                qf[ks][0] = sq[(g & 1) * 128 + ks * 8 + t];
                qf[ks][1] = sq[(g & 1) * 128 + ks * 8 + 4 + t];
            }
            const int row = (warp & 1) * 16 + (lane & 7) + (mi & 1) * 8;
            const uint32_t rowoff = sbase + row * 128, sw = lane & 7, uhi = lane >> 4;
            float sc[4] = {0.f, 0.f, 0.f, 0.f};
#pragma unroll 1
            for (int op = OP_K + (warp >> 1); op < OP_V; op += 4) {
                const int slot = op < NR ? op : op - NR;
                mbar_wait(full + slot * 8, op >= NR);
                const uint32_t base = rowoff + slot * TILE_BYTES;
                float c0[4] = {0.f, 0.f, 0.f, 0.f}, c1[4] = {0.f, 0.f, 0.f, 0.f};
#pragma unroll
                for (int ks = 0; ks < 16; ks++) {
                    uint32_t a[4];
                    ldsm4(base + (ks >> 2) * 4096 + ((((ks & 3) * 2 + uhi) ^ sw) << 4), a);
                    mma16816((ks & 1) ? c1 : c0, a, qf[ks][0], qf[ks][1]);
                }
                if (lane == 0) mbar_arrive(empty + slot * 8, 4);
                sc[0] = sc[1]; sc[1] = sc[2]; sc[2] = sc[3];
                sc[3] = bf16r(sel4(c0, t) + sel4(c1, t));
            }
            if (tid == 0) TS(3);
            float mx = fmaxf(fmaxf(sc[0], sc[1]), fmaxf(sc[2], sc[3]));
#pragma unroll
            for (int o = 2; o < 32; o <<= 1) mx = fmaxf(mx, __shfl_xor_sync(0xffffffffu, mx, o));
            float* sML = reinterpret_cast<float*>(sm + OFF_ML) + (t & 1) * 8;
            if (lane < 2) sML[warp] = mx;
            bar_sync(1, 256);
            const float4 m0 = *reinterpret_cast<const float4*>(sML), m1 = *reinterpret_cast<const float4*>(sML + 4);
            mx = fmaxf(fmaxf(fmaxf(m0.x, m0.y), fmaxf(m0.z, m0.w)), fmaxf(fmaxf(m1.x, m1.y), fmaxf(m1.z, m1.w)));
            __nv_bfloat16* sP = reinterpret_cast<__nv_bfloat16*>(sm + OFF_P) + (warp >> 1) * 64 + ((t & 1) * 4 + (g >> 1)) * 8 +
                                (warp & 1) * 4 + (t >> 1) * 2 + (g & 1);
            float l = 0.f;
#pragma unroll
            for (int i = 0; i < 4; i++) {
                const float e = ex2((sc[i] - mx) * SC);
                l += e;
                sP[i * 256] = __float2bfloat16_rn(e);
            }
#pragma unroll
            for (int o = 2; o < 32; o <<= 1) l += __shfl_xor_sync(0xffffffffu, l, o);
            if (lane < 2) sML[16 + warp] = l;
            bar_sync(2, 288);
        }
        if (tid == 0) TS(4);
        const uint32_t* ph = g_h + (hkv * 7 + warp) * 64 + (lane & 7) * 4;
        uint4 hv0 = make_uint4(tag, tag, tag, tag), hv1 = hv0;
        uint32_t* go = g_o + (hkv * 8 + warp) * 1024;
        uint32_t* gst = go + sp * 128 + (t & 1) * 64 + (t >> 1) * 32 + b * 16 + g * 2;
        go += lane * 4;
        uint32_t toff = sbase + (OP_T - 2 * NR) * TILE_BYTES + (warp * 32 + krow) * 64 + (((mi & 1) ^ ((krow >> 1) & 3)) << 4);
        uint32_t sO = sbase + OFF_W + (warp * 64 + (t & 1) * 32 + (t >> 1) * 16 + g) * 4;
        asm volatile("" : "+l"(go), "+l"(gst), "+r"(toff), "+r"(sO));
        float o0[4] = {0.f, 0.f, 0.f, 0.f}, o1[4] = {0.f, 0.f, 0.f, 0.f};
        float o2[4] = {0.f, 0.f, 0.f, 0.f}, o3[4] = {0.f, 0.f, 0.f, 0.f};
        const uint4* sP4 = reinterpret_cast<const uint4*>(sm + OFF_P) + (g & 1) * 4 + t;
        const uint32_t off0 = sbase + (warp >> 1) * 4096 + krow * 128 + ((((warp & 1) * 4 + (mi & 1)) ^ (lane & 7)) << 4);
        float r = 0.f;
#pragma unroll 1
        for (int tl = 0; tl < 16; tl++) {
            const int slot = tl < 2 * NR - OP_V ? tl + OP_V - NR : tl + OP_V - 2 * NR;
            const uint4 pf = sP4[tl * 8];
            if (tl == 8 && warp < 7) { hv0 = ld_relaxed4(ph); hv1 = ld_relaxed4(ph + 32); }
            if (tl == 15) {
                mbar_wait(hold + 8, 0);
                r = *reinterpret_cast<const volatile float*>(sm + OFF_TAG + 8 + (t & 1) * 4);
                int it = 0;
                while (!(ok4(hv0, tag) && ok4(hv1, tag)) && ++it < SPIN_MAX) { hv0 = ld_relaxed4(ph); hv1 = ld_relaxed4(ph + 32); }
                __syncwarp();
            }
            uint32_t base = off0 + slot * TILE_BYTES;
            asm volatile("" : "+r"(base));
            mbar_wait(full + slot * 8, tl < 2 * NR - OP_V);
            uint32_t af[2][4][4];
            ldsm4t(base, af[0][0]);
            ldsm4t(base ^ 32, af[0][1]);
            ldsm4t(base + 2048, af[0][2]);
            ldsm4t((base ^ 32) + 2048, af[0][3]);
            mma16816(o0, af[0][0], pf.x, pf.y);
            mma16816(o1, af[0][1], pf.x, pf.y);
            mma16816(o2, af[0][2], pf.z, pf.w);
            mma16816(o3, af[0][3], pf.z, pf.w);
            if (tl < 2 * NR - OP_V && lane == 0) mbar_arrive(empty + slot * 8, 1);
            if (tl != CLR_ && tl != 15) continue;
            const bool real = tl == 15;
            const uint32_t tg = real ? tag : 0;
            st_relaxed2(gst, tagf(pick(o0, o1, o2, o3, t, 0) * r, tg), tagf(pick(o0, o1, o2, o3, t, 2) * r, tg));
            if (!has_tail) continue;
            uint4 ov[8];
#pragma unroll
            for (int i = 0; i < 8; i++) {
                ov[i] = make_uint4(0, 0, 0, 0);
                if (PRE_) ld_relaxed4_if(ov[i], go + i * 128, real);
            }
            if (HOLD_ && lane == 0 && real) mbar_arrive(hold, 1);
            if (tid == 0) TS(5);
            const uint32_t tbar = real ? full + (OP_T - 2 * NR) * 8 : hold, tst = real ? 8 : 0;
            float c0[4] = {0.f, 0.f, 0.f, 0.f}, c1[4] = {0.f, 0.f, 0.f, 0.f};
            float c2[4] = {0.f, 0.f, 0.f, 0.f}, c3[4] = {0.f, 0.f, 0.f, 0.f};
            if (warp < 7) {
                mbar_wait(tbar, !real);
                ldsm4t(toff, af[0][0]);
                ldsm4t(toff ^ 32, af[0][1]);
                ldsm4t(toff + 1024, af[0][2]);
                ldsm4t((toff ^ 32) + 1024, af[0][3]);
                const uint32_t h0 = __byte_perm(hv0.x, hv0.y, 0x7632), h1 = __byte_perm(hv0.z, hv0.w, 0x7632);
                const uint32_t h2 = __byte_perm(hv1.x, hv1.y, 0x7632), h3 = __byte_perm(hv1.z, hv1.w, 0x7632);
                mma16816(c0, af[0][0], h0, h1);
                mma16816(c1, af[0][1], h0, h1);
                mma16816(c2, af[0][2], h2, h3);
                mma16816(c3, af[0][3], h2, h3);
            }
#pragma unroll
            for (int h = 0; h < 2; h++) {
                mbar_wait(tbar + (h + 1) * tst, !real);
                if (h == 0) {
#pragma unroll
                    for (int i = 0; i < 8; i++) ld_relaxed4_if(ov[i], go + i * 128, real && !ok4(ov[i], tag));
                }
                ldsm4t(toff + (h + 1) * TILE_BYTES, af[h][0]);
                ldsm4t((toff ^ 32) + (h + 1) * TILE_BYTES, af[h][1]);
                ldsm4t(toff + (h + 1) * TILE_BYTES + 1024, af[h][2]);
                ldsm4t((toff ^ 32) + (h + 1) * TILE_BYTES + 1024, af[h][3]);
            }
            if (tid == 0) TS(16);
            uint32_t ulo, uhi;
#pragma unroll 1
            for (int it = real ? 0 : SPIN_MAX - 1; it < SPIN_MAX; it++) {
                uint32_t bad = 0;
#pragma unroll
                for (int i = 0; i < 8; i++) bad |= (ov[i].x ^ tag) | (ov[i].y ^ tag) | (ov[i].z ^ tag) | (ov[i].w ^ tag);
#define SUM8(f) (((__uint_as_float(ov[0].f) + __uint_as_float(ov[1].f)) + (__uint_as_float(ov[2].f) + __uint_as_float(ov[3].f))) + \
                 ((__uint_as_float(ov[4].f) + __uint_as_float(ov[5].f)) + (__uint_as_float(ov[6].f) + __uint_as_float(ov[7].f))))
                ulo = packbf(SUM8(x), SUM8(z));
                uhi = packbf(SUM8(y), SUM8(w));
                if (tid == 0 && it < 6) TS(17 + it);
                if (__all_sync(0xffffffffu, (bad & 3u) == 0)) break;
#pragma unroll
                for (int i = 0; i < 8; i++) ld_relaxed4_if(ov[i], go + i * 128, real && !ok4(ov[i], tag));
            }
#pragma unroll
            for (int h = 0; h < 2; h++) {
                const uint32_t b0 = __shfl_sync(0xffffffffu, ulo, h * 16 + (lane & 7)), b1 = __shfl_sync(0xffffffffu, uhi, h * 16 + (lane & 7));
                const uint32_t b2 = __shfl_sync(0xffffffffu, ulo, h * 16 + 8 + (lane & 7)), b3 = __shfl_sync(0xffffffffu, uhi, h * 16 + 8 + (lane & 7));
                mma16816(c0, af[h][0], b0, b1);
                mma16816(c1, af[h][1], b0, b1);
                mma16816(c2, af[h][2], b2, b3);
                mma16816(c3, af[h][3], b2, b3);
            }
            asm volatile("{\n.reg .pred p;\nsetp.ne.u32 p, %3, 0;\nst.shared.f32 [%0], %1;\nst.shared.f32 [%0+32], %2;\n@p bar.arrive 3, 288;\n}"
                         ::"r"(sO), "f"(pick(c0, c1, c2, c3, t, 0)), "f"(pick(c0, c1, c2, c3, t, 2)), "r"((uint32_t)real) : "memory");
            if (tid == 0) TS(7);
        }
    } else {
        const unsigned epoch = *reinterpret_cast<volatile unsigned*>(&g_epoch[hkv * 32]);
        const uint32_t tag = epoch % 3u + 1u;
        if (lane == 0) *reinterpret_cast<uint2*>(sm + OFF_TAG) = make_uint2(tag, epoch);
        bar_sync(4, NTHREADS);
        if (has_ffn) {
            const uint32_t off = sbase + OP_G * TILE_BYTES + krow * 32 + (((mi & 1) ^ ((krow >> 2) & 1)) << 4);
            float gu[2];
#pragma unroll 1
            for (int mat = 0; mat < 2; mat++) {
                float c0[4] = {0.f, 0.f, 0.f, 0.f}, c1[4] = {0.f, 0.f, 0.f, 0.f};
                mbar_wait(full + (OP_G + mat) * 8, 0);
#pragma unroll 2
                for (int ks = 0; ks < 28; ks += 2) {
                    uint32_t a0[4], a1[4];
                    ldsm4t(off + mat * TILE_BYTES + ks * 512, a0);
                    ldsm4t(off + mat * TILE_BYTES + ks * 512 + 512, a1);
                    mma16816(c0, a0, sx[ks * 8], sx[ks * 8 + 4]);
                    mma16816(c1, a1, sx[ks * 8 + 8], sx[ks * 8 + 12]);
                }
                gu[1] = bf16r(sel4(c0, t) + sel4(c1, t));
                if (mat == 0) gu[0] = gu[1];
            }
            st_relaxed(g_h + (hkv * 14 + j16 - 2) * 32 + ((t & 1) * 4 + (g >> 1)) * 4 + (t >> 1) * 2 + (g & 1), tagbf(gu[0] * gu[1], tag));
            if (lane == 0) TS(10);
        }
        if (lane < 2) mbar_arrive(empty + (OP_G + lane) * 8, 8);
        if (!has_ffn) mbar_wait(full + 4 * 8, 0);
        if (lane < 8) st_relaxed(g_ml + cta * 8 + lane, 0);
        uint32_t* po = reinterpret_cast<uint32_t*>(out) + (lane >> 4) * 224 + j16 * 16 + (lane & 15);
        uint32_t xv = 0;
        if (hkv == 0 && has_tail) xv = __ldg(reinterpret_cast<const uint32_t*>(x) + (lane >> 4) * 224 + j16 * 16 + (lane & 15));
        bar_sync(2, 288);
        {
            float v = reinterpret_cast<const float*>(sm + OFF_ML)[lane];
#pragma unroll
            for (int o = 1; o < 8; o <<= 1) {
                const float w = __shfl_xor_sync(0xffffffffu, v, o);
                v = lane < 16 ? fmaxf(v, w) : v + w;
            }
            if ((lane & 7) == 0) st_relaxed(g_ml + cta * 8 + mi, tagf(v, tag));
            if (hkv == 0 && has_tail) {
                st_relaxed(po, xv);
                __syncwarp();
                if (lane == 0) asm volatile("fence.acq_rel.gpu;\nst.relaxed.gpu.global.u32 [%0], %1;" ::"l"(g_init + j16), "r"(tag) : "memory");
            }
            const uint32_t* pm = g_ml + (cta & ~7) * 8 + (lane & 7) * 8;
            uint4 ml;
            int it = 0;
            do { ml = ld_relaxed4(pm); } while (!ok4(ml, tag) && ++it < SPIN_MAX);
            __syncwarp();
            const float m = untag((lane & 8) ? ml.y : ml.x);
            float M = m;
#pragma unroll
            for (int o = 1; o < 8; o <<= 1) M = fmaxf(M, __shfl_xor_sync(0xffffffffu, M, o));
            const float e = ex2((m - M) * SC);
            float L = e * untag((lane & 8) ? ml.w : ml.z);
#pragma unroll
            for (int o = 1; o < 8; o <<= 1) L += __shfl_xor_sync(0xffffffffu, L, o);
            if (lane < 16 && (lane & 7) == sp) reinterpret_cast<float*>(sm + OFF_TAG + 8)[mi] = __fdiv_rn(e, L);
            __syncwarp();
            if (lane == 0) mbar_arrive(hold + 8, 1);
            if (lane == 0) TS(6);
        }
        if (has_tail) {
            uint32_t f;
            int it = 0;
            do {
                asm volatile("ld.acquire.gpu.global.u32 %0, [%1];" : "=r"(f) : "l"(g_init + j16) : "memory");
            } while (f != tag && ++it < SPIN_MAX);
            __syncwarp();
#pragma unroll 1
            for (int pass = 0; pass < 2; pass++) {
            if (pass) bar_sync(3, 288);
            const uint32_t sO2 = sbase + OFF_W + lane * 8;
            float2 u[8];
#pragma unroll
            for (int k = 0; k < 8; k++) asm volatile("ld.shared.v2.f32 {%0,%1}, [%2];" : "=f"(u[k].x), "=f"(u[k].y) : "r"(sO2 + k * 256) : "memory");
            const float y0 = ((u[0].x + u[1].x) + (u[2].x + u[3].x)) + ((u[4].x + u[5].x) + (u[6].x + u[7].x));
            const float y1 = ((u[0].y + u[1].y) + (u[2].y + u[3].y)) + ((u[4].y + u[5].y) + (u[6].y + u[7].y));
            asm volatile("{\n.reg .pred p;\nsetp.ne.u32 p, %2, 0;\n@p red.relaxed.gpu.global.add.noftz.bf16x2 [%0], %1;\n}" ::"l"(po), "r"(packbf(y0, y1)), "r"(pass) : "memory");
            }
            if (j16 == 0 && lane == 0) *reinterpret_cast<volatile unsigned*>(&g_epoch[hkv * 32]) = epoch + 1;
            if (lane == 0) TS(8);
        }
    }
}

typedef CUresult (*EncodeFn)(CUtensorMap*, CUtensorMapDataType, cuuint32_t, void*, const cuuint64_t*, const cuuint64_t*,
                             const cuuint32_t*, const cuuint32_t*, CUtensorMapInterleave, CUtensorMapSwizzle,
                             CUtensorMapL2promotion, CUtensorMapFloatOOBfill);

void make_map(EncodeFn enc, CUtensorMap* m, const void* ptr, uint64_t d0, uint64_t d1, uint64_t d2, uint64_t s1, uint64_t s2,
              uint32_t b0, uint32_t b1, uint32_t b2, CUtensorMapL2promotion promo) {
    cuuint64_t gd[3] = {d0, d1, d2};
    cuuint64_t gs[2] = {s1, s2};
    cuuint32_t bx[3] = {b0, b1, b2};
    cuuint32_t es[3] = {1, 1, 1};
    enc(m, CU_TENSOR_MAP_DATA_TYPE_BFLOAT16, 3, const_cast<void*>(ptr), gd, gs, bx, es, CU_TENSOR_MAP_INTERLEAVE_NONE,
        b0 == 64 ? CU_TENSOR_MAP_SWIZZLE_128B : b0 == 32 ? CU_TENSOR_MAP_SWIZZLE_64B : CU_TENSOR_MAP_SWIZZLE_32B, promo,
        CU_TENSOR_MAP_FLOAT_OOB_FILL_NONE);
}

}

extern "C" void kernel_launch(void* const* d_in, const int* in_sizes, int n_in, void* d_out, int out_size) {
    (void)in_sizes; (void)n_in; (void)out_size;
    static EncodeFn enc = nullptr;
    static Maps maps;
    static const void* cached[9] = {};
    if (!enc) {
        cudaDriverEntryPointQueryResult qr;
        void* fn = nullptr;
        cudaGetDriverEntryPoint("cuTensorMapEncodeTiled", &fn, cudaEnableDefault, &qr);
        enc = (EncodeFn)fn;
        cudaFuncSetAttribute(fused_decode_kernel, cudaFuncAttributeMaxDynamicSharedMemorySize, SMEM_BYTES);
    }
    bool same = true;
    for (int i = 0; i < 9; i++) same = same && cached[i] == d_in[i];
    if (!same) {
        const uint64_t R = (uint64_t)16 * SK;
        const CUtensorMapL2promotion P128 = CU_TENSOR_MAP_L2_PROMOTION_L2_128B, P256 = CU_TENSOR_MAP_L2_PROMOTION_L2_256B;
        make_map(enc, &maps.m[0], d_in[1], 64, R, 4, 512, 128, 64, 32, 4, P256);
        make_map(enc, &maps.m[1], d_in[2], 64, R, 4, 512, 128, 64, 32, 4, P256);
        make_map(enc, &maps.m[2], d_in[3], QD, D_, 1, QD * 2, (uint64_t)D_ * QD * 2, 32, 224, 1, P256);
        make_map(enc, &maps.m[3], d_in[6], FF, 224, 2, FF * 2, 224 * FF * 2, 16, 224, 2, P256);
        make_map(enc, &maps.m[4], d_in[7], FF, 224, 2, FF * 2, 224 * FF * 2, 16, 224, 2, P256);
        make_map(enc, &maps.m[5], d_in[8], D_, FF, 1, D_ * 2, (uint64_t)FF * D_ * 2, 32, 224, 1, P128);
        make_map(enc, &maps.m[6], d_in[4], D_, QD, 1, D_ * 2, (uint64_t)QD * D_ * 2, 32, 256, 1, P128);
        for (int i = 0; i < 9; i++) cached[i] = d_in[i];
    }
    fused_decode_kernel<<<NCTA, NTHREADS, SMEM_BYTES>>>(maps, (const __nv_bfloat16*)d_in[0], (__nv_bfloat16*)d_out);
}
```

```cpp
#include <cuda_runtime.h>
#include <cuda_bf16.h>
#include <cuda.h>
#include <stdint.h>

namespace {

constexpr int D_   = 448;
constexpr int SK   = 32768;
constexpr int WIN  = 4096;
constexpr int FF   = 1792;
constexpr int QD   = 4096;
constexpr int NCTA = 128;

constexpr int TILE_BYTES = 16384;
constexpr int WT_BYTES   = 14336;
constexpr int NR         = 13;
constexpr int LIM = 2, LMAX = 5;
constexpr int TAU = 1152;
constexpr int OP_G = 2, OP_K = 4, OP_V = 20, OP_T = 36, NOPS = 41;

constexpr int NTHREADS = 384;
constexpr int SPIN_MAX = 1 << 20;
constexpr float SC = 0.0625f * 1.4426950408889634f;

constexpr int OFF_P    = NR * TILE_BYTES;
constexpr int OFF_W    = OFF_P + 8192;
constexpr int OFF_H    = OFF_W + 2560;
constexpr int OFF_XN   = OFF_H + 1024;
constexpr int OFF_ML   = OFF_XN + 1792;
constexpr int OFF_TAG  = OFF_ML + 128;
constexpr int OFF_CLK  = OFF_TAG + 16;
constexpr int OFF_BAR  = OFF_CLK + 8;
constexpr int SMEM_BYTES = OFF_BAR + (2 * NR + 7) * 8;

struct Maps { CUtensorMap m[7]; };

struct Scratch {
    unsigned epoch[8 * 32];
    uint32_t q[2 * QD];
    uint32_t sc[16 * WIN * 2];
    uint32_t ml[8 * 32 * 4];
    uint32_t h[2 * FF];
    uint32_t pada[256];
    float4 acc[8 * 512];
    uint32_t padp[3872];
    uint32_t prog[64];
    uint32_t init[32];
};
__device__ __align__(128) Scratch g_scratch;

__device__ __forceinline__ uint32_t s2u(const void* p) { return (uint32_t)__cvta_generic_to_shared(p); }
__device__ __forceinline__ void mbar_init(uint32_t bar, int cnt) { asm volatile("mbarrier.init.shared::cta.b64 [%0], %1;" ::"r"(bar), "r"(cnt) : "memory"); }
__device__ __forceinline__ void mbar_expect(uint32_t bar, uint32_t bytes) { asm volatile("mbarrier.arrive.expect_tx.shared::cta.b64 _, [%0], %1;" ::"r"(bar), "r"(bytes) : "memory"); }
__device__ __forceinline__ void mbar_arrive(uint32_t bar, uint32_t cnt) { asm volatile("mbarrier.arrive.shared::cta.b64 _, [%0], %1;" ::"r"(bar), "r"(cnt) : "memory"); }
__device__ __forceinline__ void mbar_wait(uint32_t bar, uint32_t parity, uint32_t n0 = 0) {
    asm volatile("{\n.reg .pred p, q;\n.reg .u32 n;\nmov.u32 n, %2;\n"
                 "W_%=:\nmbarrier.try_wait.parity.shared::cta.b64 p, [%0], %1;\n"
                 "add.u32 n, n, 1;\nsetp.lt.u32 q, n, 0x400000;\nand.pred q, q, !p;\n@q bra W_%=;\n}"
                 ::"r"(bar), "r"(parity), "r"(n0) : "memory");
}
__device__ __forceinline__ void mbar_timer(uint32_t bar, uint32_t parity) {
    asm volatile("{\n.reg .pred p, q;\n.reg .u32 n;\nmov.u32 n, 0;\n"
                 "W_%=:\nmbarrier.try_wait.parity.shared::cta.b64 p, [%0], %1, 1000;\n"
                 "add.u32 n, n, 1;\nsetp.lt.u32 q, n, 8;\nand.pred q, q, !p;\n@q bra W_%=;\n}"
                 ::"r"(bar), "r"(parity) : "memory");
}
__device__ __forceinline__ uint32_t max2(uint32_t a, uint32_t b) { uint32_t r; asm("max.bf16x2 %0, %1, %2;" : "=r"(r) : "r"(a), "r"(b)); return r; }
__device__ __forceinline__ uint32_t clock32() { uint32_t t; asm volatile("mov.u32 %0, %clock;" : "=r"(t) :: "memory"); return t; }
__device__ __forceinline__ float ex2(float v) { float r; asm("ex2.approx.ftz.f32 %0, %1;" : "=f"(r) : "f"(v)); return r; }
__device__ __forceinline__ void tma3d(uint32_t dst, const CUtensorMap* tm, int c0, int c1, uint32_t bar, uint64_t pol) {
    asm volatile("cp.async.bulk.tensor.3d.shared::cluster.global.mbarrier::complete_tx::bytes.L2::cache_hint [%0], [%1, {%3,%4,%5}], [%2], %6;"
                 ::"r"(dst), "l"(tm), "r"(bar), "r"(c0), "r"(c1), "r"(0), "l"(pol) : "memory");
}
__device__ __forceinline__ void bar_sync(int id, int n) { asm volatile("bar.sync %0, %1;" ::"r"(id), "r"(n) : "memory"); }
__device__ __forceinline__ void bar_arrive(int id, int n) { asm volatile("bar.arrive %0, %1;" ::"r"(id), "r"(n) : "memory"); }
__device__ __forceinline__ void ldsm4(uint32_t addr, uint32_t* r) {
    asm volatile("ldmatrix.sync.aligned.m8n8.x4.shared.b16 {%0,%1,%2,%3}, [%4];"
                 : "=r"(r[0]), "=r"(r[1]), "=r"(r[2]), "=r"(r[3]) : "r"(addr) : "memory");
}
__device__ __forceinline__ void ldsm4t(uint32_t addr, uint32_t* r) {
    asm volatile("ldmatrix.sync.aligned.m8n8.x4.trans.shared.b16 {%0,%1,%2,%3}, [%4];"
                 : "=r"(r[0]), "=r"(r[1]), "=r"(r[2]), "=r"(r[3]) : "r"(addr) : "memory");
}
__device__ __forceinline__ void mma16816(float* c, const uint32_t* a, uint32_t b0, uint32_t b1) {
    asm volatile("mma.sync.aligned.m16n8k16.row.col.f32.bf16.bf16.f32 {%0,%1,%2,%3}, {%4,%5,%6,%7}, {%8,%9}, {%0,%1,%2,%3};"
                 : "+f"(c[0]), "+f"(c[1]), "+f"(c[2]), "+f"(c[3])
                 : "r"(a[0]), "r"(a[1]), "r"(a[2]), "r"(a[3]), "r"(b0), "r"(b1));
}
__device__ __forceinline__ uint4 ld_relaxed4(const uint32_t* p) {
    uint4 v;
    asm volatile("ld.relaxed.gpu.global.v4.u32 {%0,%1,%2,%3}, [%4];" : "=r"(v.x), "=r"(v.y), "=r"(v.z), "=r"(v.w) : "l"(p) : "memory");
    return v;
}
__device__ __forceinline__ void ld_relaxed4_if(uint4& v, const uint32_t* p, bool c) {
    asm volatile("{\n.reg .pred p;\nsetp.ne.u32 p, %5, 0;\n@p ld.relaxed.gpu.global.v4.u32 {%0,%1,%2,%3}, [%4];\n}"
                 : "+r"(v.x), "+r"(v.y), "+r"(v.z), "+r"(v.w) : "l"(p), "r"((uint32_t)c) : "memory");
}
__device__ __forceinline__ void st_relaxed(uint32_t* p, uint32_t v) { asm volatile("st.relaxed.gpu.global.u32 [%0], %1;" ::"l"(p), "r"(v) : "memory"); }
__device__ __forceinline__ void st_relaxed2(uint32_t* p, uint32_t a, uint32_t b) { asm volatile("st.relaxed.gpu.global.v2.u32 [%0], {%1,%2};" ::"l"(p), "r"(a), "r"(b) : "memory"); }
__device__ __forceinline__ float bf16r(float v) { return __bfloat162float(__float2bfloat16_rn(v)); }
__device__ __forceinline__ float bflo(uint32_t w) { return __uint_as_float(w << 16); }
__device__ __forceinline__ float bfhi(uint32_t w) { return __uint_as_float(w & 0xffff0000u); }
__device__ __forceinline__ uint32_t packbf(float lo, float hi) {
    __nv_bfloat162 v = __floats2bfloat162_rn(lo, hi);
    return *reinterpret_cast<uint32_t*>(&v);
}
__device__ __forceinline__ float sel4(const float* c, int t) { return (t & 2) ? ((t & 1) ? c[3] : c[2]) : ((t & 1) ? c[1] : c[0]); }
__device__ __forceinline__ float pick(const float* o0, const float* o1, const float* o2, const float* o3, int t, int i) {
    const float a = (t & 2) ? ((t & 1) ? o1[i + 1] : o1[i]) : ((t & 1) ? o0[i + 1] : o0[i]);
    const float c = (t & 2) ? ((t & 1) ? o3[i + 1] : o3[i]) : ((t & 1) ? o2[i + 1] : o2[i]);
    return a + c;
}
__device__ __forceinline__ uint32_t tagf(float v, uint32_t tag) { return (__float_as_uint(v) & ~3u) | tag; }
__device__ __forceinline__ uint32_t tagbf(float v, uint32_t tag) { return packbf(0.f, v) | tag; }
__device__ __forceinline__ float untag(uint32_t w) { return __uint_as_float(w & ~3u); }
__device__ __forceinline__ bool ok4(const uint4& v, uint32_t tag) { return (((v.x ^ tag) | (v.y ^ tag) | (v.z ^ tag) | (v.w ^ tag)) & 3u) == 0; }

__device__ __forceinline__ int slot_of(int i) { return i < NR ? i : i < 2 * NR ? i - NR : i - 2 * NR; }
__device__ __forceinline__ uint32_t par_of(int i) { return i >= NR && i < 2 * NR; }

__global__ void __launch_bounds__(NTHREADS, 1)
fused_decode_kernel(const __grid_constant__ Maps maps, const __nv_bfloat16* __restrict__ x, __nv_bfloat16* __restrict__ out, Scratch* __restrict__ gs) {
    extern __shared__ __align__(1024) unsigned char sm[];
    const uint32_t sbase = s2u(sm);
    const int cta = blockIdx.x;
    const int hkv = cta >> 4, j16 = cta & 15, b = j16 >> 3;
    const bool has_ffn = j16 >= 2, has_tail = j16 < 14;
    const uint32_t full = sbase + OFF_BAR, empty = full + NR * 8, hold = empty + NR * 8;

    uint64_t polF;
    asm volatile("createpolicy.fractional.L2::evict_first.b64 %0, 1.0;" : "=l"(polF));
    {
        const uint32_t f0 = __shfl_sync(0xffffffffu, threadIdx.x < 32 ? full : sbase + OFF_P + threadIdx.x, 0);
#pragma unroll
        for (int i = 0; i < 4; i++) mbar_init(f0 + i * 8, 1);
        asm volatile("fence.mbarrier_init.release.cluster;" ::: "memory");
    }
    if (threadIdx.x == 0) {
#pragma unroll
        for (int i = 0; i < 4; i++) {
            if (i < 2 || has_ffn)
                tma3d(sbase + i * TILE_BYTES, &maps.m[i < 2 ? 2 : i + 1], i < 2 ? cta * 32 : hkv * 224 + (j16 - 2) * 16, i == 1 ? 224 : 0,
                      full + i * 8, polF);
        }
#pragma unroll
        for (int i = 0; i < 4; i++) mbar_expect(full + i * 8, i < 2 || has_ffn ? WT_BYTES : 0);
    }
    const int tid = threadIdx.x < 128 ? threadIdx.x + 256 : threadIdx.x - 128, warp = tid >> 5, lane = tid & 31;
    if (warp == 8) {
        if (lane == 0) {
#pragma unroll
            for (int i = 4; i < 2 * NR + 7; i++) mbar_init(full + i * 8, i < NR || i > 2 * NR ? 1 : 8);
            asm volatile("fence.mbarrier_init.release.cluster;" ::: "memory");
        }
        if (lane == 0) asm volatile("st.shared.v2.u32 [%0], {%1, %2};" ::"r"(sbase + OFF_CLK), "r"(clock32() + 800), "r"(0) : "memory");
        __syncwarp();
        bar_arrive(4, NTHREADS);
        const int nops = has_tail ? NOPS : OP_T;
        if (lane == 0) {
#pragma unroll 1
            for (int i = OP_K; i < nops; i++) {
                const int slot = i > OP_T ? (i - 15) >> 1 : slot_of(i);
                int map, c0, c1;
                uint32_t bytes = TILE_BYTES;
                if (i < OP_V) { map = 0; c0 = 0; c1 = (i - OP_K) * SK + (SK - WIN) + cta * 32; }
                else if (i < OP_T) { map = 1; c0 = (cta & 3) * 64; c1 = ((i & 1) * 8 + ((i - OP_V) >> 1)) * SK + (SK - WIN) + (cta >> 2) * 128; }
                else if (i == OP_T) { map = 5; c0 = j16 * 32; c1 = hkv * 224; bytes = WT_BYTES; }
                else { map = 6; c0 = j16 * 32; c1 = hkv * 512 + (i - OP_T - 1) * 128; bytes = 8192; }
                const uint32_t bar = i >= OP_T ? hold + 16 + (i - OP_T) * 8 : full + slot * 8;
                if (i >= NR) mbar_wait(empty + slot * 8, i >= 2 * NR);
                if (i >= LMAX) mbar_wait(full + slot_of(min(i, OP_T + 2) - LMAX) * 8, par_of(i - LMAX));
                mbar_expect(bar, bytes);
                const int il = i > OP_T ? OP_T - 1 + (0x2110 >> (i - OP_T - 1) * 4 & 15) : i - LIM;
                const uint32_t lb = il >= OP_T ? hold + 16 + (il - OP_T) * 8 : full + slot_of(il) * 8, lp = par_of(il);
                const int thr = ((i > OP_T ? 4 * (i + OP_T + 1) - 2 : 8 * i) - (i < OP_V ? 18 : 17)) * (TAU / 8);
                asm volatile("{\n.reg .pred p, q;\n.reg .u32 n, a, c;\nmov.u32 n, 0;\n"
                             "P_%=:\nmbarrier.test_wait.parity.shared::cta.b64 p, [%0], %1;\n"
                             "ld.volatile.shared.u32 a, [%2];\nmov.u32 c, %clock;\nsub.u32 c, c, a;\nsetp.ge.or.s32 p, c, %3, p;\n"
                             "add.u32 n, n, 1;\nsetp.lt.u32 q, n, 0x1000000;\nand.pred q, q, !p;\n@q bra P_%=;\n}"
                             ::"r"(lb), "r"(lp), "r"(sbase + OFF_CLK), "r"(thr) : "memory");
                tma3d(sbase + (i > OP_T ? (i - 15) * 8192 : slot * TILE_BYTES), &maps.m[map], c0, c1, bar, polF);
                asm volatile("st.shared.u32 [%0], %1;" ::"r"(sbase + OFF_CLK + 4), "r"((uint32_t)(i >= min(nops - 1, OP_T))) : "memory");
            }
        }
        return;
    }
    if (warp == 11) {
        bar_sync(4, NTHREADS);
        if (lane == 0) {
            uint32_t* prog = gs->prog + (*reinterpret_cast<const volatile uint32_t*>(sm + OFF_TAG + 4) & 1) * 32;
#pragma unroll 1
            for (int i = 0; i < OP_T; i++) {
                mbar_wait(full + slot_of(i) * 8, par_of(i));
                if (((cta + i) & 3) == 0) asm volatile("red.relaxed.gpu.global.add.u32 [%0], %1;" ::"l"(prog), "r"(4) : "memory");
            }
        }
        __syncwarp();
        return;
    }
    const int g = lane >> 2, t = lane & 3, mi = lane >> 3;
    const int krow = (mi >> 1) * 8 + (lane & 7);
    const uint32_t* sx = reinterpret_cast<const uint32_t*>(sm + OFF_XN) + (g & 1) * 224 + t;

    if (warp < 8) {
        uint32_t* gq = gs->q + ((((t & 1) * 8 + hkv) * 4 + (cta & 1) * 2 + warp) * 32 + ((cta & 6) + b) * 4 + (g >> 1)) * 4 + (t >> 1) * 2 + (g & 1);
        {
            const int bb = warp >> 2;
            const uint4 xa = __ldg(reinterpret_cast<const uint4*>(x + bb * D_) + lane);
            uint4 xb = make_uint4(0, 0, 0, 0);
            if (lane < 24) xb = __ldg(reinterpret_cast<const uint4*>(x + bb * D_) + 32 + lane);
            const int i4 = tid & 127;
            uint2 xo = make_uint2(0, 0);
            if (i4 < 112) xo = __ldg(reinterpret_cast<const uint2*>(x + bb * D_) + i4);
            const uint32_t e[8] = {xa.x, xa.y, xa.z, xa.w, xb.x, xb.y, xb.z, xb.w};
            float s = 0.f;
#pragma unroll
            for (int j = 0; j < 8; j++) s += bflo(e[j]) + bfhi(e[j]);
#pragma unroll
            for (int o = 16; o; o >>= 1) s += __shfl_xor_sync(0xffffffffu, s, o);
            const float mean = s * (1.f / D_);
            float v = 0.f;
#pragma unroll
            for (int j = 0; j < 8; j++) {
                const float d0 = bflo(e[j]) - mean, d1 = bfhi(e[j]) - mean;
                if (j < 4 || lane < 24) v += d0 * d0 + d1 * d1;
            }
#pragma unroll
            for (int o = 16; o; o >>= 1) v += __shfl_xor_sync(0xffffffffu, v, o);
            const float mb = bf16r(mean);
            const float den = bf16r(sqrtf(bf16r(bf16r(v * (1.f / D_)) + 1e-5f)));
            const uint32_t n0 = packbf(__fdiv_rn(bf16r(bflo(xo.x) - mb), den), __fdiv_rn(bf16r(bfhi(xo.x) - mb), den));
            const uint32_t n1 = packbf(__fdiv_rn(bf16r(bflo(xo.y) - mb), den), __fdiv_rn(bf16r(bfhi(xo.y) - mb), den));
            if (i4 < 112) reinterpret_cast<uint2*>(sm + OFF_XN + bb * 896)[i4] = make_uint2(n0, n1);
        }
        bar_sync(4, NTHREADS);
        const uint32_t tag = *reinterpret_cast<const volatile uint32_t*>(sm + OFF_TAG);

        if (warp < 2) {
            const uint32_t off = sbase + krow * 64 + (((warp * 2 + (mi & 1)) ^ ((krow >> 1) & 3)) << 4);
            float c0[4] = {0.f, 0.f, 0.f, 0.f}, c1[4] = {0.f, 0.f, 0.f, 0.f};
#pragma unroll 1
            for (int hf = 0; hf < 2; hf++) {
                mbar_wait(full + hf * 8, 0);
#pragma unroll
                for (int ks = 0; ks < 14; ks++) {
                    uint32_t a[4];
                    ldsm4t(off + hf * TILE_BYTES + ks * 1024, a);
                    mma16816((ks & 1) ? c1 : c0, a, sx[hf * 112 + ks * 8], sx[hf * 112 + ks * 8 + 4]);
                }
            }
            st_relaxed(gq, tagbf(sel4(c0, t) + sel4(c1, t), tag));
            if (lane < 2) mbar_arrive(empty + lane * 8, 4);
        }

        const bool pub = (warp & 3) == (cta & 3);
        float zl[4];
        {
            const uint32_t rowoff = sbase + ((lane & 7) + (mi & 1) * 8) * 128, sw = lane & 7, uhi = lane >> 4;
            mbar_wait(full + max(OP_K + warp, 7) * 8, 0);
            if (pub && lane < 16) asm volatile("st.relaxed.gpu.global.v4.u32 [%0], {%1,%1,%1,%1};" ::"l"(gs->acc + warp * 512 + (cta >> 2) * 16 + lane), "r"(0) : "memory");
#pragma unroll 1
            for (int op = OP_K + warp; op < OP_V; op += 8) {
                const uint32_t* p = gs->q + (op - OP_K) * 512 + lane * 4;
                uint4 v[4];
                int it = 0;
                do {
#pragma unroll
                    for (int i = 0; i < 4; i++) v[i] = ld_relaxed4(p + i * 128);
                } while (!(ok4(v[0], tag) && ok4(v[1], tag) && ok4(v[2], tag) && ok4(v[3], tag)) && ++it < SPIN_MAX);
                __syncwarp();
                uint32_t qf[4][2];
#pragma unroll
                for (int i = 0; i < 4; i++) { qf[i][0] = __byte_perm(v[i].x, v[i].y, 0x7632); qf[i][1] = __byte_perm(v[i].z, v[i].w, 0x7632); }
                const int slot = op < NR ? op : op - NR;
                mbar_wait(full + slot * 8, op >= NR);
                const uint32_t base = rowoff + slot * TILE_BYTES;
                float r0[4], r1[4];
#pragma unroll
                for (int qt = 0; qt < 4; qt++) {
                    float c0[4] = {0.f, 0.f, 0.f, 0.f}, c1[4] = {0.f, 0.f, 0.f, 0.f};
#pragma unroll
                    for (int ks = 0; ks < 4; ks++) {
                        uint32_t a0[4], a1[4];
                        ldsm4(base + qt * 4096 + (((ks * 2 + uhi) ^ sw) << 4), a0);
                        ldsm4(base + qt * 4096 + 2048 + (((ks * 2 + uhi) ^ sw) << 4), a1);
                        mma16816(c0, a0, qf[ks][0], qf[ks][1]);
                        mma16816(c1, a1, qf[ks][0], qf[ks][1]);
                    }
#pragma unroll
                    for (int k = 0; k < 4; k++)
                        if (qt == 0 || t == qt) { r0[k] = c0[k]; r1[k] = c1[k]; }
                }
                if (lane == 0) mbar_arrive(empty + slot * 8, 8);
#pragma unroll
                for (int k = 0; k < 4; k++) r0[k] = ((t & 2) ? r1[k] : r0[k]) + __shfl_xor_sync(0xffffffffu, (t & 2) ? r0[k] : r1[k], 2);
#pragma unroll
                for (int k = 0; k < 2; k++) r0[k] = ((t & 1) ? r0[k + 2] : r0[k]) + __shfl_xor_sync(0xffffffffu, (t & 1) ? r0[k] : r0[k + 2], 1);
                st_relaxed2(gs->sc + ((op - OP_K) * WIN + cta * 32 + t * 8 + g) * 2, tagbf(r0[0], tag), tagbf(r0[1], tag));
            }
            const uint32_t* ps = gs->sc + (warp * WIN + (cta >> 2) * 128) * 2 + lane * 4;
            __syncwarp();
            if (pub) asm volatile("fence.acq_rel.gpu;" ::: "memory");
            mbar_timer(full + (warp + 15 - NR) * 8, 1);
            uint4 v[4];
            int it = 0;
            do {
#pragma unroll
                for (int i = 0; i < 4; i++) v[i] = ld_relaxed4(ps + (i >> 1) * (16 * WIN) + (i & 1) * 128);
            } while (!(ok4(v[0], tag) && ok4(v[1], tag) && ok4(v[2], tag) && ok4(v[3], tag)) && ++it < SPIN_MAX);
            __syncwarp();
            uint32_t m[2];
            float l[4] = {0.f, 0.f, 0.f, 0.f};
#pragma unroll
            for (int i = 0; i < 2; i++)
                m[i] = max2(max2(__byte_perm(v[2 * i].x, v[2 * i].y, 0x7632), __byte_perm(v[2 * i].z, v[2 * i].w, 0x7632)),
                            max2(__byte_perm(v[2 * i + 1].x, v[2 * i + 1].y, 0x7632), __byte_perm(v[2 * i + 1].z, v[2 * i + 1].w, 0x7632)));
#pragma unroll 1
            for (int o = 1; o < 32; o <<= 1) { m[0] = max2(m[0], __shfl_xor_sync(0xffffffffu, m[0], o)); m[1] = max2(m[1], __shfl_xor_sync(0xffffffffu, m[1], o)); }
            uint32_t* sP = reinterpret_cast<uint32_t*>(sm + OFF_P) + (warp * 8 + (lane >> 4)) * 32 + (lane & 3) * 4 + ((lane >> 2) & 3);
#pragma unroll
            for (int i = 0; i < 4; i++) {
                const float x0 = bflo(m[i >> 1]), x1 = bfhi(m[i >> 1]);
                const float e0 = ex2((bfhi(v[i].x) - x0) * SC), e1 = ex2((bfhi(v[i].y) - x1) * SC);
                const float e2 = ex2((bfhi(v[i].z) - x0) * SC), e3 = ex2((bfhi(v[i].w) - x1) * SC);
                sP[i * 64] = packbf(e0, e2);
                sP[i * 64 + 16] = packbf(e1, e3);
                l[i & 2] += e0 + e2;
                l[(i & 2) + 1] += e1 + e3;
                zl[i] = ((i & 1) ? x1 : x0) * SC;
            }
#pragma unroll 1
            for (int o = 1; o < 32; o <<= 1) {
#pragma unroll
                for (int k = 0; k < 4; k++) l[k] += __shfl_xor_sync(0xffffffffu, l[k], o);
            }
            if (pub && lane < 4) st_relaxed(gs->ml + warp * 128 + (cta >> 2) * 4 + lane, tagf(sel4(zl, t) + __log2f(sel4(l, t)), tag));
            if (warp < 4) mbar_wait(full + (23 - NR) * 8, 1);
        }
        const float4* go = gs->acc + (hkv * 8 + warp) * 64 + (lane >> 2) * 8 + t;
        float4* gst = gs->acc + ((t & 1) * 4 + (cta & 3)) * 64 + (warp & 3) * 16 + (warp >> 2) * 8 + g;
        const int wrow = (krow & 8) + ((krow >> 1) & 3) + (krow & 1) * 4;
        uint32_t toff = sbase + (OP_T + 1 - 2 * NR) * TILE_BYTES + (warp * 64 + wrow) * 64 + (((mi & 1) ^ ((wrow >> 1) & 3)) << 4);
        uint32_t sO = sbase + OFF_W + (warp * 64 + (t & 1) * 32 + (t >> 1) * 16 + g) * 4;
        asm volatile("" : "+l"(go), "+l"(gst), "+r"(toff), "+r"(sO));
        const uint4* sP4 = reinterpret_cast<const uint4*>(sm + OFF_P) + (g & 1) * 4 + t;
        const uint32_t off0 = sbase + krow * 128 + ((((warp & 3) * 2 + (mi & 1)) ^ (lane & 7)) << 4);
        const float* sF = reinterpret_cast<const float*>(sm + OFF_ML) + (t & 1);
#pragma unroll 1
        for (int tl = warp >> 2; tl < 16; tl += 2) {
            if (tl >> 1 == (warp & 4)) {
                uint4 v;
                int it = 0;
                do {
                    asm volatile("ld.acquire.gpu.global.v4.u32 {%0,%1,%2,%3}, [%4];" : "=r"(v.x), "=r"(v.y), "=r"(v.z), "=r"(v.w) : "l"(gs->ml + warp * 128 + lane * 4) : "memory");
                } while (!ok4(v, tag) && ++it < SPIN_MAX);
                __syncwarp();
                float z[4] = {untag(v.x), untag(v.y), untag(v.z), untag(v.w)}, M[4] = {z[0], z[1], z[2], z[3]};
#pragma unroll 1
                for (int o = 1; o < 32; o <<= 1) {
#pragma unroll
                    for (int k = 0; k < 4; k++) M[k] = fmaxf(M[k], __shfl_xor_sync(0xffffffffu, M[k], o));
                }
#pragma unroll
                for (int k = 0; k < 4; k++) z[k] = ex2(z[k] - M[k]);
#pragma unroll 1
                for (int o = 1; o < 32; o <<= 1) {
#pragma unroll
                    for (int k = 0; k < 4; k++) z[k] += __shfl_xor_sync(0xffffffffu, z[k], o);
                }
                if (lane < 4) reinterpret_cast<float*>(sm + OFF_ML)[warp * 4 + lane] = __fdividef(ex2(sel4(zl, t) - sel4(M, t)), sel4(z, t));
            }
            if ((tl & 6) == 0) bar_sync(1, 256);
            if (((tl - 8) | j16 | tid) == 0)
                *reinterpret_cast<volatile unsigned*>(&gs->epoch[hkv * 32]) = *reinterpret_cast<const volatile uint32_t*>(sm + OFF_TAG + 4) + 1;
            const float f = *reinterpret_cast<const volatile float*>(sF + tl * 2);
            const int slot = tl < 2 * NR - OP_V ? tl + OP_V - NR : tl + OP_V - 2 * NR;
            uint4 pf[4];
#pragma unroll
            for (int i = 0; i < 4; i++) pf[i] = sP4[tl * 32 + i * 8];
            uint32_t base = off0 + slot * TILE_BYTES;
            asm volatile("" : "+r"(base));
            mbar_wait(full + slot * 8, tl < 2 * NR - OP_V);
            uint32_t af[8][4];
#pragma unroll
            for (int k = 0; k < 8; k++) ldsm4t(base + k * 2048, af[k]);
            float o0[4] = {0.f, 0.f, 0.f, 0.f}, o1[4] = {0.f, 0.f, 0.f, 0.f};
            float o2[4] = {0.f, 0.f, 0.f, 0.f}, o3[4] = {0.f, 0.f, 0.f, 0.f};
#pragma unroll
            for (int h = 0; h < 2; h++) {
                mma16816(o0, af[h * 4 + 0], pf[h * 2].x, pf[h * 2].y);
                mma16816(o1, af[h * 4 + 1], pf[h * 2].z, pf[h * 2].w);
                mma16816(o2, af[h * 4 + 2], pf[h * 2 + 1].x, pf[h * 2 + 1].y);
                mma16816(o3, af[h * 4 + 3], pf[h * 2 + 1].z, pf[h * 2 + 1].w);
            }
#pragma unroll
            for (int k = 0; k < 4; k++) o0[k] = (o0[k] + o1[k]) + (o2[k] + o3[k]);
            const float oa = (t & 1) ? o0[1] : o0[0], ob = (t & 1) ? o0[3] : o0[2];
            asm volatile("{\n.reg .pred p;\nsetp.ne.u32 p, %3, 0;\n@p red.relaxed.gpu.global.add.v4.f32 [%0], {%1,%2,%4,%4};\n}"
                         ::"l"(gst + (tl >> 1) * 512), "f"(oa * f), "f"(ob * f), "r"((uint32_t)(t < 2)), "f"(1.f) : "memory");
            if (tl < 2 * NR - OP_V && lane == 0) mbar_arrive(empty + slot * 8, 2);
            if (tl >> 1 != 5 && tl < 14) continue;
            const bool real = tl >= 14;
            if (!has_tail) continue;
            const uint32_t own = real ? hold + 24 + (warp >> 1) * 8 : hold;
            mbar_wait(real ? full + (OP_T - 1 - 2 * NR) * 8 : hold, !real);
            uint32_t ulo, uhi;
#pragma unroll 1
            for (int it = real ? 0 : SPIN_MAX - 1; it < SPIN_MAX; it++) {
                uint4 ra = make_uint4(0, 0, 0, 0), rb = ra;
                ld_relaxed4_if(ra, (const uint32_t*)go, real); ld_relaxed4_if(rb, (const uint32_t*)(go + 4), real);
                ulo = packbf(__uint_as_float(ra.x), __uint_as_float(rb.x));
                uhi = packbf(__uint_as_float(ra.y), __uint_as_float(rb.y));
                if (__all_sync(0xffffffffu, ((ra.z & ra.w & rb.z & rb.w) == 0x42000000u))) break;
            }
            uint32_t bf[8];
#pragma unroll
            for (int k = 0; k < 8; k++) bf[k] = __shfl_sync(0xffffffffu, (k & 1) ? uhi : ulo, (k >> 1) * 8 + (lane & 7));
            mbar_wait(own, !real, (bf[0] ^ bf[1] ^ bf[2] ^ bf[3] ^ bf[4] ^ bf[5] ^ bf[6] ^ bf[7]) & 1);
#pragma unroll
            for (int k = 0; k < 8; k++) ldsm4t((toff ^ ((k & 1) * 32)) + (k >> 1) * 1024, af[k]);
            float c0[4] = {0.f, 0.f, 0.f, 0.f}, c1[4] = {0.f, 0.f, 0.f, 0.f};
            float c2[4] = {0.f, 0.f, 0.f, 0.f}, c3[4] = {0.f, 0.f, 0.f, 0.f};
#pragma unroll
            for (int h = 0; h < 2; h++) {
                mma16816(c0, af[h * 4 + 0], bf[h * 4], bf[h * 4 + 1]);
                mma16816(c1, af[h * 4 + 1], bf[h * 4], bf[h * 4 + 1]);
                mma16816(c2, af[h * 4 + 2], bf[h * 4 + 2], bf[h * 4 + 3]);
                mma16816(c3, af[h * 4 + 3], bf[h * 4 + 2], bf[h * 4 + 3]);
            }
            asm volatile("{\n.reg .pred p, q;\nsetp.ge.u32 p, %3, 21;\nsetp.ge.u32 q, %4, 14;\nand.pred q, q, !p;\nst.shared.f32 [%0], %1;\nst.shared.f32 [%0+32], %2;\n@p bar.arrive 5, 96;\n@q bar.arrive 3, 256;\n}"
                         ::"r"(sO), "f"(pick(c0, c1, c2, c3, t, 0)), "f"(pick(c0, c1, c2, c3, t, 2)), "r"(tl + warp), "r"(tl) : "memory");
        }
    } else {
        uint32_t* po = reinterpret_cast<uint32_t*>(out) + (lane >> 4) * 224 + j16 * 16 + (lane & 15);
        if (warp == 10) {
            bar_sync(4, NTHREADS);
            if (lane == 0) {
                volatile uint32_t* clk = reinterpret_cast<volatile uint32_t*>(sm + OFF_CLK);
                const uint32_t* prog = gs->prog + (*reinterpret_cast<const volatile uint32_t*>(sm + OFF_TAG + 4) & 1) * 32;
                mbar_wait(full + 4 * 8, 0);
#pragma unroll 1
                for (int it = 0; it < 256 && !clk[1]; it++) {
                    const uint32_t now = clock32();
                    uint32_t c;
                    asm volatile("ld.relaxed.gpu.global.u32 %0, [%1];" : "=r"(c) : "l"(prog) : "memory");
                    clk[0] = now - (c * TAU >> 7);
                    __nanosleep(200);
                }
            }
            __syncwarp();
            if (!has_tail) return;
            mbar_wait(hold + 8, 0);
        } else {
        const unsigned epoch = *reinterpret_cast<volatile unsigned*>(&gs->epoch[hkv * 32]);
        const uint32_t tag = epoch % 3u + 1u;
        if (lane == 0) *reinterpret_cast<uint2*>(sm + OFF_TAG) = make_uint2(tag, epoch);
        bar_sync(4, NTHREADS);
        if (has_ffn) {
            const uint32_t off = sbase + OP_G * TILE_BYTES + krow * 32 + (((mi & 1) ^ ((krow >> 2) & 1)) << 4);
            float gu[2];
#pragma unroll 1
            for (int mat = 0; mat < 2; mat++) {
                float c0[4] = {0.f, 0.f, 0.f, 0.f}, c1[4] = {0.f, 0.f, 0.f, 0.f};
                mbar_wait(full + (OP_G + mat) * 8, 0);
#pragma unroll 2
                for (int ks = 0; ks < 28; ks += 2) {
                    uint32_t a0[4], a1[4];
                    ldsm4t(off + mat * TILE_BYTES + ks * 512, a0);
                    ldsm4t(off + mat * TILE_BYTES + ks * 512 + 512, a1);
                    mma16816(c0, a0, sx[ks * 8], sx[ks * 8 + 4]);
                    mma16816(c1, a1, sx[ks * 8 + 8], sx[ks * 8 + 12]);
                }
                gu[1] = bf16r(sel4(c0, t) + sel4(c1, t));
                if (mat == 0) gu[0] = gu[1];
            }
            st_relaxed(gs->h + (hkv * 14 + j16 - 2) * 32 + ((t & 1) * 4 + (g >> 1)) * 4 + (t >> 1) * 2 + (g & 1), tagbf(gu[0] * gu[1], tag));
        }
        if (lane < 2) mbar_arrive(empty + (OP_G + lane) * 8, 8);
        if (!has_ffn) mbar_wait(full + 4 * 8, 0);
        if (cta == 0 && lane == 8) st_relaxed(gs->prog + (~epoch & 1) * 32, 0);
        uint32_t xv = 0;
        if (hkv == 0 && has_tail) xv = __ldg(reinterpret_cast<const uint32_t*>(x) + (lane >> 4) * 224 + j16 * 16 + (lane & 15));
        mbar_wait(full + 10 * 8, 0);
        if (has_tail) {
            uint4 v[4];
            int it = 0;
            do {
#pragma unroll
                for (int i = 0; i < 4; i++) v[i] = ld_relaxed4(gs->h + hkv * 448 + (i < 3 ? i * 32 + lane : 96 + (lane & 15)) * 4);
            } while (!(ok4(v[0], tag) && ok4(v[1], tag) && ok4(v[2], tag) && ok4(v[3], tag)) && ++it < SPIN_MAX);
#pragma unroll
            for (int i = 0; i < 4; i++)
                reinterpret_cast<uint2*>(sm + OFF_H)[i * 32 + lane] = make_uint2(__byte_perm(v[i].x, v[i].y, 0x7632), __byte_perm(v[i].z, v[i].w, 0x7632));
            __syncwarp();
        }
        if (hkv == 0 && has_tail) {
            st_relaxed(po, xv);
            __syncwarp();
            if (lane == 0) asm volatile("fence.acq_rel.gpu;\nst.relaxed.gpu.global.u32 [%0], %1;" ::"l"(gs->init + j16), "r"(tag) : "memory");
        }
        if (lane == 0) mbar_arrive(hold + 8, 1);
        mbar_timer(full + (OP_V - NR) * 8, 1);
        if (!has_tail) return;
        uint32_t f;
        int it = 0;
        do {
            asm volatile("ld.acquire.gpu.global.u32 %0, [%1];" : "=r"(f) : "l"(gs->init + j16) : "memory");
        } while (f != tag && ++it < SPIN_MAX);
        __syncwarp();
        }
        uint2 hf[7];
#pragma unroll
        for (int k = 0; k < 7; k++) hf[k] = reinterpret_cast<const uint2*>(sm + OFF_H)[((warp - 9) * 7 + k) * 8 + (lane & 7)];
        const uint32_t toff = sbase + (OP_T - 2 * NR) * TILE_BYTES + ((warp - 9) * 112 + krow) * 64 + (((mi & 1) ^ ((krow >> 1) & 3)) << 4);
        const uint32_t sO = sbase + OFF_W + ((warp - 1) * 64 + (t & 1) * 32 + (t >> 1) * 16 + g) * 4;
        uint32_t sO2 = sbase + OFF_W + lane * 8;
        asm volatile("" : "+l"(po), "+r"(sO2));
#pragma unroll 1
        for (int pass = warp - 9; pass < 2; pass++) {
            mbar_wait(hold + 8 + pass * 8, 0);
            float c0[4] = {0.f, 0.f, 0.f, 0.f}, c1[4] = {0.f, 0.f, 0.f, 0.f};
            float c2[4] = {0.f, 0.f, 0.f, 0.f}, c3[4] = {0.f, 0.f, 0.f, 0.f};
#pragma unroll
            for (int k = 0; k < 7; k++) {
                uint32_t a0[4], a1[4];
                ldsm4t(toff + k * 1024, a0);
                ldsm4t((toff ^ 32) + k * 1024, a1);
                mma16816((k & 1) ? c2 : c0, a0, hf[k].x, hf[k].y);
                mma16816((k & 1) ? c3 : c1, a1, hf[k].x, hf[k].y);
            }
            asm volatile("st.shared.f32 [%0], %1;\nst.shared.f32 [%0+32], %2;"
                         ::"r"(sO), "f"(pick(c0, c1, c2, c3, t, 0)), "f"(pick(c0, c1, c2, c3, t, 2)) : "memory");
            if (warp == 10) { bar_arrive(3, 256); return; }
            if (pass) bar_sync(3, 256);
            float2 u[10];
#pragma unroll
            for (int k = 0; k < 8; k++) asm volatile("ld.shared.v2.f32 {%0,%1}, [%2];" : "=f"(u[k].x), "=f"(u[k].y) : "r"(sO2 + (k < 6 ? k : k + 2) * 256) : "memory");
            float y0 = ((u[0].x + u[1].x) + (u[2].x + u[3].x)) + ((u[4].x + u[5].x) + (u[6].x + u[7].x)), y1 = ((u[0].y + u[1].y) + (u[2].y + u[3].y)) + ((u[4].y + u[5].y) + (u[6].y + u[7].y));
            asm volatile("{\n.reg .pred p;\nsetp.ne.u32 p, %2, 0;\n@p bar.sync 5, 96;\n}" : "+f"(y0), "+f"(y1) : "r"(pass) : "memory");
#pragma unroll
            for (int k = 8; k < 10; k++) asm volatile("ld.shared.v2.f32 {%0,%1}, [%2];" : "=f"(u[k].x), "=f"(u[k].y) : "r"(sO2 + (k - 2) * 256) : "memory");
            y0 = (y0 + u[8].x) + u[9].x;
            y1 = (y1 + u[8].y) + u[9].y;
            asm volatile("{\n.reg .pred p;\nsetp.ne.u32 p, %2, 0;\n@p red.relaxed.gpu.global.add.noftz.bf16x2 [%0], %1;\n@p exit;\nst.shared.u32 [%3], %1;\n}" ::"l"(po), "r"(packbf(y0, y1)), "r"(pass), "r"(sO2 + 2048) : "memory");
        }
    }
}

typedef CUresult (*EncodeFn)(CUtensorMap*, CUtensorMapDataType, cuuint32_t, void*, const cuuint64_t*, const cuuint64_t*,
                             const cuuint32_t*, const cuuint32_t*, CUtensorMapInterleave, CUtensorMapSwizzle,
                             CUtensorMapL2promotion, CUtensorMapFloatOOBfill);

void make_map(EncodeFn enc, CUtensorMap* m, const void* ptr, uint64_t d0, uint64_t d1, uint64_t d2, uint64_t s1, uint64_t s2,
              uint32_t b0, uint32_t b1, uint32_t b2, CUtensorMapL2promotion promo) {
    cuuint64_t gd[3] = {d0, d1, d2};
    cuuint64_t gs[2] = {s1, s2};
    cuuint32_t bx[3] = {b0, b1, b2};
    cuuint32_t es[3] = {1, 1, 1};
    enc(m, CU_TENSOR_MAP_DATA_TYPE_BFLOAT16, 3, const_cast<void*>(ptr), gd, gs, bx, es, CU_TENSOR_MAP_INTERLEAVE_NONE,
        b0 == 64 ? CU_TENSOR_MAP_SWIZZLE_128B : b0 == 32 ? CU_TENSOR_MAP_SWIZZLE_64B : CU_TENSOR_MAP_SWIZZLE_32B, promo,
        CU_TENSOR_MAP_FLOAT_OOB_FILL_NONE);
}

}

extern "C" void kernel_launch(void* const* d_in, const int* in_sizes, int n_in, void* d_out, int out_size) {
    (void)in_sizes; (void)n_in; (void)out_size;
    static EncodeFn enc = nullptr;
    static Maps maps;
    static const void* cached[9] = {};
    static void* scratch = nullptr;
    if (!enc) {
        cudaDriverEntryPointQueryResult qr;
        void* fn = nullptr;
        cudaGetDriverEntryPoint("cuTensorMapEncodeTiled", &fn, cudaEnableDefault, &qr);
        enc = (EncodeFn)fn;
        cudaGetSymbolAddress(&scratch, g_scratch);
        cudaFuncSetAttribute(fused_decode_kernel, cudaFuncAttributeMaxDynamicSharedMemorySize, SMEM_BYTES);
    }
    bool same = true;
    for (int i = 0; i < 9; i++) same = same && cached[i] == d_in[i];
    if (!same) {
        const uint64_t R = (uint64_t)16 * SK;
        const CUtensorMapL2promotion P128 = CU_TENSOR_MAP_L2_PROMOTION_L2_128B, P256 = CU_TENSOR_MAP_L2_PROMOTION_L2_256B;
        make_map(enc, &maps.m[0], d_in[1], 64, R, 4, 512, 128, 64, 32, 4, P128);
        make_map(enc, &maps.m[1], d_in[2], 256, R, 1, 512, R * 512, 64, 128, 1, P128);
        make_map(enc, &maps.m[2], d_in[3], QD, D_, 1, QD * 2, (uint64_t)D_ * QD * 2, 32, 224, 1, P256);
        make_map(enc, &maps.m[3], d_in[6], FF, 224, 2, FF * 2, 224 * FF * 2, 16, 224, 2, P256);
        make_map(enc, &maps.m[4], d_in[7], FF, 224, 2, FF * 2, 224 * FF * 2, 16, 224, 2, P256);
        make_map(enc, &maps.m[5], d_in[8], D_, FF, 1, D_ * 2, (uint64_t)FF * D_ * 2, 32, 224, 1, P128);
        make_map(enc, &maps.m[6], d_in[4], D_, QD, 1, D_ * 2, (uint64_t)QD * D_ * 2, 32, 128, 1, P128);
        for (int i = 0; i < 9; i++) cached[i] = d_in[i];
    }
    fused_decode_kernel<<<NCTA, NTHREADS, SMEM_BYTES>>>(maps, (const __nv_bfloat16*)d_in[0], (__nv_bfloat16*)d_out, (Scratch*)scratch);
}
```
